```python
import torch

def _softmax(x, axis=-1):
    return torch.softmax(x, dim=axis)

def _gelu(x):
    return torch.nn.functional.gelu(x, approximate='tanh')

def _silu(x):
    return torch.nn.functional.silu(x)

def _sigmoid(x):
    return torch.sigmoid(x)

def _layernorm(x, axis=-1, eps=1e-05):
    m = x.mean(dim=axis, keepdim=True)
    v = x.var(dim=axis, keepdim=True, unbiased=False)
    return (x - m) / torch.sqrt(v + eps)

def _scatter_add(tgt, idx, src, axis=0):
    return tgt.clone().index_add_(axis, idx, src)

def _segment_sum(src, seg, n):
    out = torch.zeros((n,) + src.shape[1:], dtype=src.dtype)
    return out.index_add_(0, seg, src)

def _pad(x, pw):
    flat = tuple((v for pair in reversed(pw) for v in pair))
    return torch.nn.functional.pad(x, flat)
kernel_name = 'gated_mix__memory_aug_recurrent_mem_tr__ssm_conv_h3__prompt'

def setup_inputs():

    _w = lambda a: (lambda t: t.to(torch.bfloat16) if t.is_floating_point() else t)(torch.as_tensor(a))

    def _A_setup():
        B, S, Dm = (1, 2048, 640)
        H, Dh = (32, 128)
        M, seg = (8, 32)
        seg = min(seg, S)
        S = S // seg * seg
        return {'x': _w((lambda *s: torch.randn(*s, dtype=torch.bfloat16) * 0.05)(B, S, Dm)), 'mem0': _w((lambda *s: torch.randn(*s, dtype=torch.bfloat16) * 0.4)(B, M, Dm)), 'Wq': _w((lambda *s: torch.randn(*s, dtype=torch.bfloat16) * 6.4)(Dm, H, Dh) * Dm ** (-0.5)), 'Wk': _w((lambda *s: torch.randn(*s, dtype=torch.bfloat16) * 6.4)(Dm, H, Dh) * Dm ** (-0.5)), 'Wv': _w((lambda *s: torch.randn(*s, dtype=torch.bfloat16) * 0.4)(Dm, H, Dh) * Dm ** (-0.5)), 'Wo': _w((lambda *s: torch.randn(*s, dtype=torch.bfloat16) * 0.4)(H, Dh, Dm) * (H * Dh) ** (-0.5)), 'seg_len': seg}
    _A_in = _A_setup()

    def _B_setup():
        B, S, D = (1, 2048, 640)
        ks = 4
        return {'q': _w((lambda *s: torch.randn(*s, dtype=torch.bfloat16) * 0.05)(B, S, D)), 'k': _w((lambda *s: torch.randn(*s, dtype=torch.bfloat16) * 0.4)(B, S, D)), 'v': _w((lambda *s: torch.randn(*s, dtype=torch.bfloat16) * 0.4)(B, S, D)), 'shift_k': _w((lambda *s: torch.randn(*s, dtype=torch.bfloat16) * 0.4)(D, ks) * 0.5), 'ssm_k': _w((lambda *s: torch.randn(*s, dtype=torch.bfloat16) * 0.4)(D, S) * (1.0 / S ** 0.5)), 'ssm_D': _w((lambda *s: torch.randn(*s, dtype=torch.bfloat16) * 0.4)(D))}
    _B_in = _B_setup()
    return {'A_x': _A_in['x'], 'A_mem0': _A_in['mem0'], 'A_Wq': _A_in['Wq'], 'A_Wk': _A_in['Wk'], 'A_Wv': _A_in['Wv'], 'A_Wo': _A_in['Wo'], 'A_seg_len': _A_in['seg_len'], 'B_q': _B_in['q'], 'B_k': _B_in['k'], 'B_v': _B_in['v'], 'B_shift_k': _B_in['shift_k'], 'B_ssm_k': _B_in['ssm_k'], 'B_ssm_D': _B_in['ssm_D'], 'gate_w': _w((lambda *s: torch.randn(*s, dtype=torch.bfloat16) * 0.05)(640) * 16.0)}

def reference(A_x, A_mem0, A_Wq, A_Wk, A_Wv, A_Wo, A_seg_len, B_q, B_k, B_v, B_shift_k, B_ssm_k, B_ssm_D, gate_w):

    def _A_ref(x, mem0, Wq, Wk, Wv, Wo, seg_len):
        B, S, Dm = x.shape
        H, Dh = (Wq.shape[1], Wq.shape[2])
        M = mem0.shape[1]
        scale = Dh ** (-0.5)
        n_seg = S // seg_len
        L = M + seg_len
        idx = torch.arange(L)
        mask = (idx[:, None] < M) | (idx[:, None] >= idx[None, :])
        mem = mem0
        outs = []
        for s in range(n_seg):
            xs = x[:, s * seg_len:(s + 1) * seg_len, :].clone()
            h = torch.concatenate([mem, xs], axis=1)
            q = torch.einsum('btd,dhe->bhte', h, Wq)
            k = torch.einsum('btd,dhe->bhte', h, Wk)
            v = torch.einsum('btd,dhe->bhte', h, Wv)
            scores = torch.einsum('bhqe,bhke->bhqk', q, k) * scale
            scores = torch.where(mask[None, None], scores, -1000000000.0)
            p = _softmax(scores, axis=-1)
            o = torch.einsum('bhqk,bhke->bhqe', p, v)
            o = torch.einsum('bhte,hed->btd', o, Wo)
            mem = o[:, :M, :].clone()
            outs.append(o[:, M:, :])
        return torch.concatenate(outs, axis=1)

    def _B_ref(q, k, v, shift_k, ssm_k, ssm_D):
        B, S, D = q.shape
        ks = shift_k.shape[-1]
        k_pad = _pad(k, ((0, 0), (ks - 1, 0), (0, 0)))
        k_shift = torch.zeros_like(k)
        for t in range(ks):
            k_shift = k_shift + k_pad[:, t:t + S, :] * shift_k[:, ks - 1 - t][None, None, :]
        kv = k_shift * v
        L = 2 * S
        kv_pad = _pad(kv, ((0, 0), (0, S), (0, 0)))
        kf_pad = _pad(ssm_k, ((0, 0), (0, S)))
        kv_f = (lambda x, axes=(-2, -1): torch.fft.rfft2(x.float(), dim=axes))(kv_pad[:, None, :, :], axes=(1, 2))
        kf_f = (lambda x, axes=(-2, -1): torch.fft.rfft2(x.float(), dim=axes))(kf_pad[:, None, :], axes=(1, 2))
        kf_f = (lambda x, *d: x.permute(*d))(kf_f, 1, 2, 0)
        y_f = kv_f * kf_f[None, :, :, :]
        y = (lambda x, s, axes=(-2, -1): torch.fft.irfft2(x, s=s, dim=axes).to(torch.bfloat16))(y_f, (1, L), axes=(1, 2))[:, 0, :S, :]
        y = y + kv * ssm_D[None, None, :]
        return q * y
    x = A_x
    g = _sigmoid((x * gate_w).sum(-1, keepdims=True))
    a = _A_ref(x, A_mem0, A_Wq, A_Wk, A_Wv, A_Wo, A_seg_len)
    b = _B_ref(x, B_k, B_v, B_shift_k, B_ssm_k, B_ssm_D)
    return g * a + (1 - g) * b
```

```cpp
#include <cuda_runtime.h>
#include <cuda_bf16.h>
#include <cuda.h>
#include <stdint.h>

typedef __nv_bfloat16 bf16;

constexpr int S_ = 2048, DM_ = 640, NH_ = 32, NSEG_ = 64;
constexpr int NKG_ = 7, NCR_ = 5, NB_CTAS = NKG_ * NCR_;

#define DELAY_P 800
#define DELAY_M 800
#define BACKOFF 100
#define WGB 20
#define WGD 1
#define SPIN_LIMIT (1 << 13)
#define SPIN_FAIL(guard, code) (((++guard) & 1023) == 0 && (guard >= SPIN_LIMIT || *(volatile unsigned*)&g_misc[2] != 0) && ((g_misc[2] = (code)), true))

__device__ uint4 g_P[2][160 * 128];
__device__ uint4 g_M[4][640];
__device__ uint4 g_ox[(size_t)NSEG_ * NH_ * 512];
__device__ float g_part[(size_t)NKG_ * S_ * DM_];
__device__ bf16 g_b[(size_t)S_ * DM_];
__device__ float g_gate[S_];
__device__ unsigned g_oxcnt[NSEG_ * 8];
__device__ unsigned g_pcnt[NSEG_ * 8];
__device__ unsigned g_misc[4];
#define CAL(b, i) do {} while (0)

__device__ __forceinline__ uint32_t smem_u32(const void* p) { return (uint32_t)__cvta_generic_to_shared(p); }
__device__ __forceinline__ void mbar_init(uint32_t mb, int cnt) { asm volatile("mbarrier.init.shared.b64 [%0], %1;" ::"r"(mb), "r"(cnt)); }
__device__ __forceinline__ void mbar_expect(uint32_t mb, int bytes) { asm volatile("mbarrier.arrive.expect_tx.shared.b64 _, [%0], %1;" ::"r"(mb), "r"(bytes) : "memory"); }
__device__ __forceinline__ void mbar_arrive(uint32_t mb) { asm volatile("mbarrier.arrive.shared.b64 _, [%0];" ::"r"(mb) : "memory"); }
__device__ __forceinline__ bool mbar_try(uint32_t mb, int parity) {
    uint32_t ok;
    asm volatile("{ .reg .pred p; mbarrier.try_wait.parity.shared.b64 p, [%1], %2; selp.u32 %0, 1, 0, p; }" : "=r"(ok) : "r"(mb), "r"(parity) : "memory");
    return ok;
}
__device__ __forceinline__ void mbar_wait(uint32_t mb, int parity) {
    int guard = 0;
    while (!mbar_try(mb, parity)) { if (SPIN_FAIL(guard, 1)) break; }
}
__device__ __forceinline__ void mbar_wait_u(uint32_t mb, int parity) {
    asm volatile("{ .reg .pred p; .reg .u32 c; mov.u32 c, 0;\n"
                 "WL%=: mbarrier.try_wait.parity.shared.b64 p, [%0], %1;\n"
                 "@p bra.uni WD%=;\n"
                 "add.u32 c, c, 1; setp.lt.u32 p, c, 16384;\n"
                 "@p bra.uni WL%=;\n"
                 "WD%=: }" ::"r"(mb), "r"(parity) : "memory");
}
__device__ __forceinline__ uint32_t movm(uint32_t a) { uint32_t d; asm volatile("movmatrix.sync.aligned.m8n8.trans.b16 %0, %1;" : "=r"(d) : "r"(a)); return d; }
__device__ __forceinline__ float ex2(float x) { float y; asm("ex2.approx.ftz.f32 %0, %1;" : "=f"(y) : "f"(x)); return y; }
__device__ __forceinline__ float rcp(float x) { float y; asm("rcp.approx.ftz.f32 %0, %1;" : "=f"(y) : "f"(x)); return y; }
__device__ __forceinline__ uint32_t mapa(uint32_t a, uint32_t r) { uint32_t o; asm volatile("mapa.shared::cluster.u32 %0, %1, %2;" : "=r"(o) : "r"(a), "r"(r)); return o; }
__device__ __forceinline__ uint4 ld_poll16(const void* p) { uint4 v; asm volatile("ld.relaxed.gpu.global.v4.u32 {%0,%1,%2,%3}, [%4];" : "=r"(v.x), "=r"(v.y), "=r"(v.z), "=r"(v.w) : "l"(p) : "memory"); return v; }
__device__ __forceinline__ void st_rel16(void* p, uint4 v) { asm volatile("st.relaxed.gpu.global.v4.u32 [%0], {%1,%2,%3,%4};" ::"l"(p), "r"(v.x), "r"(v.y), "r"(v.z), "r"(v.w) : "memory"); }
__device__ __forceinline__ void st_rel4(void* p, uint32_t v) { asm volatile("st.relaxed.gpu.global.u32 [%0], %1;" ::"l"(p), "r"(v) : "memory"); }
__device__ __forceinline__ unsigned ld_acq(const unsigned* p) { unsigned v; asm volatile("ld.acquire.gpu.global.u32 %0, [%1];" : "=r"(v) : "l"(p) : "memory"); return v; }
__device__ __forceinline__ void red_rel(unsigned* p, unsigned v) { asm volatile("red.release.gpu.global.add.u32 [%0], %1;" ::"l"(p), "r"(v) : "memory"); }
__device__ __forceinline__ void bar_sync(int id, int n) { asm volatile("bar.sync %0, %1;" ::"r"(id), "r"(n) : "memory"); }
__device__ __forceinline__ void st_async8(uint32_t dst, uint32_t a, uint32_t b, uint32_t mb) {
    asm volatile("st.async.weak.shared::cluster.mbarrier::complete_tx::bytes.v2.b32 [%0], {%1,%2}, [%3];" ::"r"(dst), "r"(a), "r"(b), "r"(mb) : "memory");
}
__device__ __forceinline__ void bulk_s2s(uint32_t dst, uint32_t src, uint32_t bytes, uint32_t mb) {
    asm volatile("cp.async.bulk.shared::cluster.shared::cta.mbarrier::complete_tx::bytes [%0], [%1], %2, [%3];" ::"r"(dst), "r"(src), "r"(bytes), "r"(mb) : "memory");
}
__device__ __forceinline__ void bulk_g2s(uint32_t dst, const void* src, uint32_t bytes, uint32_t mb) {
    asm volatile("cp.async.bulk.shared::cluster.global.mbarrier::complete_tx::bytes [%0], [%1], %2, [%3];" ::"r"(dst), "l"(src), "r"(bytes), "r"(mb) : "memory");
}
__device__ __forceinline__ void tma3d(uint32_t dst, const CUtensorMap* tm, int c0, int c1, int c2, uint32_t mb) {
    asm volatile("cp.async.bulk.tensor.3d.shared::cluster.global.mbarrier::complete_tx::bytes [%0], [%1, {%3, %4, %5}], [%2];"
                 ::"r"(dst), "l"((uint64_t)tm), "r"(mb), "r"(c0), "r"(c1), "r"(c2) : "memory");
}
__device__ __forceinline__ void tma3d_mc(uint32_t dst, const CUtensorMap* tm, int c0, int c1, int c2, uint32_t mb) {
    asm volatile("cp.async.bulk.tensor.3d.shared::cluster.global.mbarrier::complete_tx::bytes.multicast::cluster [%0], [%1, {%3, %4, %5}], [%2], %6;"
                 ::"r"(dst), "l"((uint64_t)tm), "r"(mb), "r"(c0), "r"(c1), "r"(c2), "h"((uint16_t)7) : "memory");
}
__device__ __forceinline__ void st_rel8(void* p, uint32_t a, uint32_t b) { asm volatile("st.relaxed.gpu.global.v2.u32 [%0], {%1,%2};" ::"l"(p), "r"(a), "r"(b) : "memory"); }
__device__ __forceinline__ void fence_async_smem() { asm volatile("fence.proxy.async.shared::cta;" ::: "memory"); }
__device__ __forceinline__ void fence_async_all() { asm volatile("fence.proxy.async;" ::: "memory"); }
__device__ __forceinline__ void cp_async16(uint32_t dst, const void* src) { asm volatile("cp.async.cg.shared.global [%0], [%1], 16;" ::"r"(dst), "l"(src) : "memory"); }
__device__ __forceinline__ void cluster_sync() { asm volatile("barrier.cluster.arrive.aligned; barrier.cluster.wait.aligned;" ::: "memory"); }
__device__ __forceinline__ int clk() { int c; asm volatile("mov.u32 %0, %%clock;" : "=r"(c)); return c; }

__device__ __forceinline__ void ldsm4(uint32_t* r, uint32_t a) { asm volatile("ldmatrix.sync.aligned.m8n8.x4.shared.b16 {%0,%1,%2,%3}, [%4];" : "=r"(r[0]), "=r"(r[1]), "=r"(r[2]), "=r"(r[3]) : "r"(a) : "memory"); }
__device__ __forceinline__ void ldsm2(uint32_t* r, uint32_t a) { asm volatile("ldmatrix.sync.aligned.m8n8.x2.shared.b16 {%0,%1}, [%2];" : "=r"(r[0]), "=r"(r[1]) : "r"(a) : "memory"); }
__device__ __forceinline__ void ldsm4t(uint32_t* r, uint32_t a) { asm volatile("ldmatrix.sync.aligned.m8n8.x4.trans.shared.b16 {%0,%1,%2,%3}, [%4];" : "=r"(r[0]), "=r"(r[1]), "=r"(r[2]), "=r"(r[3]) : "r"(a) : "memory"); }
__device__ __forceinline__ void ldsm2t(uint32_t* r, uint32_t a) { asm volatile("ldmatrix.sync.aligned.m8n8.x2.trans.shared.b16 {%0,%1}, [%2];" : "=r"(r[0]), "=r"(r[1]) : "r"(a) : "memory"); }
__device__ __forceinline__ void stsm4t(uint32_t a, uint32_t r0, uint32_t r1, uint32_t r2, uint32_t r3) {
    asm volatile("stmatrix.sync.aligned.m8n8.x4.trans.shared.b16 [%0], {%1,%2,%3,%4};" ::"r"(a), "r"(r0), "r"(r1), "r"(r2), "r"(r3) : "memory");
}
__device__ __forceinline__ uint4 lds128(uint32_t a) { uint4 v; asm volatile("ld.shared.v4.u32 {%0,%1,%2,%3}, [%4];" : "=r"(v.x), "=r"(v.y), "=r"(v.z), "=r"(v.w) : "r"(a) : "memory"); return v; }
__device__ __forceinline__ float2 lds64f(uint32_t a) { float2 v; asm volatile("ld.shared.v2.f32 {%0,%1}, [%2];" : "=f"(v.x), "=f"(v.y) : "r"(a) : "memory"); return v; }
__device__ __forceinline__ float lds32f(uint32_t a) { float v; asm volatile("ld.shared.f32 %0, [%1];" : "=f"(v) : "r"(a) : "memory"); return v; }
__device__ __forceinline__ uint32_t lds32(uint32_t a) { uint32_t v; asm volatile("ld.shared.u32 %0, [%1];" : "=r"(v) : "r"(a) : "memory"); return v; }
__device__ __forceinline__ void sts128(uint32_t a, uint4 v) { asm volatile("st.shared.v4.u32 [%0], {%1,%2,%3,%4};" ::"r"(a), "r"(v.x), "r"(v.y), "r"(v.z), "r"(v.w) : "memory"); }
__device__ __forceinline__ void sts128f(uint32_t a, float x, float y, float z, float w) { asm volatile("st.shared.v4.f32 [%0], {%1,%2,%3,%4};" ::"r"(a), "f"(x), "f"(y), "f"(z), "f"(w) : "memory"); }
__device__ __forceinline__ void sts64f(uint32_t a, float x, float y) { asm volatile("st.shared.v2.f32 [%0], {%1,%2};" ::"r"(a), "f"(x), "f"(y) : "memory"); }
__device__ __forceinline__ void sts64(uint32_t a, uint32_t x, uint32_t y) { asm volatile("st.shared.v2.u32 [%0], {%1,%2};" ::"r"(a), "r"(x), "r"(y) : "memory"); }
__device__ __forceinline__ void sts32f(uint32_t a, float x) { asm volatile("st.shared.f32 [%0], %1;" ::"r"(a), "f"(x) : "memory"); }

__device__ __forceinline__ void mma16(float* d, const uint32_t* a, uint32_t b0, uint32_t b1) {
    asm volatile("mma.sync.aligned.m16n8k16.row.col.f32.bf16.bf16.f32 {%0,%1,%2,%3}, {%4,%5,%6,%7}, {%8,%9}, {%0,%1,%2,%3};"
                 : "+f"(d[0]), "+f"(d[1]), "+f"(d[2]), "+f"(d[3]) : "r"(a[0]), "r"(a[1]), "r"(a[2]), "r"(a[3]), "r"(b0), "r"(b1));
}
__device__ __forceinline__ void mma16r(float* d, uint32_t a0, uint32_t a1, uint32_t a2, uint32_t a3, uint32_t b0, uint32_t b1) {
    asm volatile("mma.sync.aligned.m16n8k16.row.col.f32.bf16.bf16.f32 {%0,%1,%2,%3}, {%4,%5,%6,%7}, {%8,%9}, {%0,%1,%2,%3};"
                 : "+f"(d[0]), "+f"(d[1]), "+f"(d[2]), "+f"(d[3]) : "r"(a0), "r"(a1), "r"(a2), "r"(a3), "r"(b0), "r"(b1));
}
__device__ __forceinline__ void mma8(float* d, uint32_t a0, uint32_t a1, uint32_t b0) {
    asm volatile("mma.sync.aligned.m16n8k8.row.col.f32.bf16.bf16.f32 {%0,%1,%2,%3}, {%4,%5}, {%6}, {%0,%1,%2,%3};"
                 : "+f"(d[0]), "+f"(d[1]), "+f"(d[2]), "+f"(d[3]) : "r"(a0), "r"(a1), "r"(b0));
}
__device__ __forceinline__ void wgmma_n32(float* d, const uint32_t* a, uint32_t desc_lo, int sc) {
    asm volatile("{ .reg .pred p; .reg .b64 dd; setp.ne.b32 p, %21, 0; mov.b64 dd, {%20, 0x40000040};\n"
                 "wgmma.mma_async.sync.aligned.m64n32k16.f32.bf16.bf16 {%0,%1,%2,%3,%4,%5,%6,%7,%8,%9,%10,%11,%12,%13,%14,%15}, {%16,%17,%18,%19}, dd, p, 1, 1, 0; }\n"
                 : "+f"(d[0]), "+f"(d[1]), "+f"(d[2]), "+f"(d[3]), "+f"(d[4]), "+f"(d[5]), "+f"(d[6]), "+f"(d[7]),
                   "+f"(d[8]), "+f"(d[9]), "+f"(d[10]), "+f"(d[11]), "+f"(d[12]), "+f"(d[13]), "+f"(d[14]), "+f"(d[15])
                 : "r"(a[0]), "r"(a[1]), "r"(a[2]), "r"(a[3]), "r"(desc_lo), "r"(sc));
}
#define WG_FENCE() asm volatile("wgmma.fence.sync.aligned;" ::: "memory")
#define WG_COMMIT() asm volatile("wgmma.commit_group.sync.aligned;" ::: "memory")
#define WG_WAIT0() asm volatile("wgmma.wait_group.sync.aligned 0;" ::: "memory")
__device__ __forceinline__ uint32_t desc_sw128(uint32_t saddr) { return ((saddr & 0x3FFFF) >> 4) | (1u << 16); }
__device__ __forceinline__ uint32_t pack2(float lo, float hi) { __nv_bfloat162 h = __floats2bfloat162_rn(lo, hi); return *(uint32_t*)&h; }
__device__ __forceinline__ float bflo(uint32_t u) { return __uint_as_float(u << 16); }
__device__ __forceinline__ float bfhi(uint32_t u) { return __uint_as_float(u & 0xffff0000u); }
__device__ __forceinline__ float rbf(float x) { return __uint_as_float(pack2(0.f, x)); }
__device__ __forceinline__ uint32_t nzw(uint32_t u) { return u == 0 ? 0x80008000u : u; }
__device__ __forceinline__ uint32_t min4(uint4 v) { return min(min(v.x, v.y), min(v.z, v.w)); }
__device__ __forceinline__ void mbar_arrive_if(uint32_t mb, uint32_t c) {
    asm volatile("{ .reg .pred p; setp.ne.u32 p, %1, 0; @p mbarrier.arrive.shared.b64 _, [%0]; }" ::"r"(mb), "r"(c) : "memory");
}
__device__ __forceinline__ int eperm(int p) { return (p & ~31) + 8 * ((p >> 2) & 3) + 4 * (p & 1) + 2 * ((p >> 4) & 1) + ((p >> 1) & 1); }

constexpr int XT_OFF = 0, WO_OFF = 81920, WO_STRIDE = 464, KV_OFF = 141312, KV_STRIDE = 272, KV_BYTES = 40 * KV_STRIDE,
              QX_OFF = 184832, QX_BYTES = 32 * KV_STRIDE, QM_OFF = 202240, M_OFF = 204416, SCR_OFF = 214656, BAR_OFF = 231040,
              A_SMEM = 231168;
constexpr int K_OFF = KV_OFF, V_OFF = KV_OFF + 2 * KV_BYTES;
constexpr int MB_X = BAR_OFF, MB_M = BAR_OFF + 16  , MB_V = BAR_OFF + 40, MB_WD = BAR_OFF + 48, MB_H1 = BAR_OFF + 56, MB_KV = BAR_OFF + 64,
              MB_WO = BAR_OFF + 80, MB_FREE = BAR_OFF + 88, MB_R = BAR_OFF + 104  ;
constexpr float SCALE = 0.08838834764831845f;
constexpr float LOG2E = 1.4426950408889634f;
constexpr int A_THREADS = 384;

#define FRESH_LANE() int lane = lane_r; asm volatile("" : "+r"(lane)); const int g = lane >> 2, t = lane & 3; const uint32_t l16 = lane * 16; (void)g; (void)t; (void)l16
#define PIN(x) asm volatile("" ::"r"(x))
#define TS(i) do {} while (0)
#define TSV(i, cond, val) do {} while (0)

__global__ void __cluster_dims__(3, 1, 1) __launch_bounds__(A_THREADS, 1)
rec_kernel(const __grid_constant__ CUtensorMap tmx, const bf16* __restrict__ mem0, const bf16* __restrict__ Wq,
           const bf16* __restrict__ Wk, const bf16* __restrict__ Wv, const bf16* __restrict__ Wo) {
    extern __shared__ __align__(1024) unsigned char smem[];
    const uint32_t sb = __shfl_sync(0xffffffffu, smem_u32(smem), 0);
    const int tid = threadIdx.x, warp = __shfl_sync(0xffffffffu, tid >> 5, 0);
    const int lane = tid & 31;
    const int g = lane >> 2, t = lane & 3;
    uint32_t rank; asm volatile("mov.u32 %0, %%cluster_ctarank;" : "=r"(rank));
    const int head = blockIdx.x / 3;

    asm volatile("griddepcontrol.launch_dependents;");
    CAL(blockIdx.x, 0);
    if (tid == 0) {
        mbar_init(sb + MB_X, 1); mbar_init(sb + MB_X + 8, 1);
        for (int j = 0; j < 3; j++) { mbar_init(sb + MB_M + 8 * j, 1); mbar_init(sb + MB_R + 8 * j, 1); }
        mbar_init(sb + MB_V, 3); mbar_init(sb + MB_WD, 24);
        mbar_init(sb + MB_H1, 1); mbar_init(sb + MB_KV, 1); mbar_init(sb + MB_KV + 8, 1); mbar_init(sb + MB_WO, 8);
        mbar_init(sb + MB_FREE, 2); mbar_init(sb + MB_FREE + 8, 2);
        asm volatile("fence.mbarrier_init.release.cluster;" ::: "memory");
        fence_async_smem();
        mbar_expect(sb + MB_X, 40960); mbar_expect(sb + MB_X + 8, 40960);
    }
    __syncthreads();
    cluster_sync();
    if (tid == 0) {
        for (int n = 0; n < 2; n++)
            for (int kb = rank; kb < 10; kb += 3) tma3d_mc(sb + XT_OFF + n * 40960 + kb * 4096, &tmx, 0, 32 * n, kb, sb + MB_X + 8 * n);
    }

    if (warp < 8) {
        asm volatile("setmaxnreg.inc.sync.aligned.u32 224;");
        const int lane_r = __shfl_sync(0xffffffffu, tid & 31, tid & 31);
        const int wg = warp >> 2, w = warp & 3;
        uint32_t A[2][20][4];
        {
            const bf16* W = rank == 0 ? Wq : (rank == 1 ? Wk : Wv);
            const bf16* wp = W + (size_t)(320 * wg + 2 * t) * 4096 + head * 128 + 32 * w + 4 * g;
#pragma unroll
            for (int ks = 0; ks < 20; ks++) {
                uint2 v0 = __ldg((const uint2*)(wp + (size_t)(16 * ks) * 4096));
                uint2 v1 = __ldg((const uint2*)(wp + (size_t)(16 * ks + 1) * 4096));
                uint2 v2 = __ldg((const uint2*)(wp + (size_t)(16 * ks + 8) * 4096));
                uint2 v3 = __ldg((const uint2*)(wp + (size_t)(16 * ks + 9) * 4096));
                A[0][ks][0] = v0.x; A[0][ks][1] = v1.x; A[0][ks][2] = v2.x; A[0][ks][3] = v3.x;
                A[1][ks][0] = v0.y; A[1][ks][1] = v1.y; A[1][ks][2] = v2.y; A[1][ks][3] = v3.y;
            }
#pragma unroll
            for (int ks = 0; ks < 20; ks++) {
                uint32_t r[2][4];
#pragma unroll
                for (int i = 0; i < 4; i++) { r[0][i] = wg ? A[1][ks][i] : A[0][ks][i]; r[1][i] = wg ? A[0][ks][i] : A[1][ks][i]; }
#pragma unroll
                for (int mt = 0; mt < 2; mt++) {
                    A[mt][ks][0] = __byte_perm(r[mt][0], r[mt][1], 0x5410); A[mt][ks][1] = __byte_perm(r[mt][0], r[mt][1], 0x7632);
                    A[mt][ks][2] = __byte_perm(r[mt][2], r[mt][3], 0x5410); A[mt][ks][3] = __byte_perm(r[mt][2], r[mt][3], 0x7632);
                }
            }
        }

        auto xproj = [&](int n) {
            const int st = n & 1;
            mbar_wait_u(sb + MB_X + 8 * st, (n >> 1) & 1);
            FRESH_LANE();
            float acc[2][16];
            const uint32_t d0 = __shfl_sync(0xffffffffu, desc_sw128(sb + XT_OFF + st * 40960 + wg * 5 * 4096), 0);
            WG_FENCE();
#pragma unroll
            for (int ks = 0; ks < 20; ks++) {
                const uint32_t d = d0 + (((ks >> 2) * 4096 + (ks & 3) * 32) >> 4);
                wgmma_n32(acc[1], A[1][ks], d, ks > 0);
                wgmma_n32(acc[0], A[0][ks], d, ks > 0);
            }
            WG_COMMIT();
            WG_WAIT0();
#pragma unroll
            for (int j = 0; j < 4; j++)
                sts128f(sb + SCR_OFF + warp * 2048 + j * 512 + l16, acc[1][4 * j], acc[1][4 * j + 1], acc[1][4 * j + 2], acc[1][4 * j + 3]);
            if (n >= 2) mbar_wait_u(sb + MB_FREE + 8 * st, ((n - 2) >> 1) & 1);
            bar_sync(1, 256);
            const uint32_t dstb = sb + (rank == 0 ? QX_OFF + st * QX_BYTES : (rank == 1 ? K_OFF : V_OFF) + st * KV_BYTES + 8 * KV_STRIDE);
            {
                uint4 o[4]; uint32_t pk[8];
#pragma unroll
                for (int j = 0; j < 4; j++) o[j] = lds128(sb + SCR_OFF + (warp ^ 4) * 2048 + j * 512 + l16);
#pragma unroll
                for (int j = 0; j < 4; j++) {
                    pk[2 * j] = movm(pack2(acc[0][4 * j] + __uint_as_float(o[j].x), acc[0][4 * j + 1] + __uint_as_float(o[j].y)));
                    pk[2 * j + 1] = movm(pack2(acc[0][4 * j + 2] + __uint_as_float(o[j].z), acc[0][4 * j + 3] + __uint_as_float(o[j].w)));
                }
#pragma unroll
                for (int j = 0; j < 4; j++) sts64(dstb + 8 * j * KV_STRIDE + g * KV_STRIDE + t * 8 + (32 * w + 16 * wg) * 2, pk[2 * j], pk[2 * j + 1]);
            }
            fence_async_smem();
            bar_sync(1, 256);
            if (warp == 0 && lane == 0) {
                const int a0 = (2 * n) % 3, a1 = (2 * n + 1) % 3;
                int bytes = rank == 0 ? 2 * QX_BYTES : QX_BYTES;
                if (rank != 0 && (a0 == (int)rank || a1 == (int)rank)) bytes += QX_BYTES / 2;
                const uint32_t mbkv = sb + MB_KV + 8 * st;
                mbar_expect(mbkv, bytes);
                if (rank == 0) {
                    if (a0 != 0) bulk_s2s(mapa(dstb, a0), dstb, QX_BYTES / 2, mapa(mbkv, a0));
                    if (a1 != 0) bulk_s2s(mapa(dstb + QX_BYTES / 2, a1), dstb + QX_BYTES / 2, QX_BYTES / 2, mapa(mbkv, a1));
                } else {
                    bulk_s2s(mapa(dstb, 0), dstb, QX_BYTES, mapa(mbkv, 0));
                    bulk_s2s(mapa(dstb, 3 - rank), dstb, QX_BYTES, mapa(mbkv, 3 - rank));
                }
            }
        };

        xproj(0);
#pragma unroll 1
        for (int s = 0; s < NSEG_; s++) {
            const int st = s & 1;
            if (warp == 0 && lane_r == 0) mbar_expect(sb + MB_H1, 6144);
            {
                float acc[2][2][4];
#pragma unroll
                for (int i = 0; i < 16; i++) ((float*)acc)[i] = 0.f;
                FRESH_LANE();
                const uint32_t mrd = sb + M_OFF + wg * 512 + l16;
                const uint32_t dl = sb + (rank == 0 ? QM_OFF : (rank == 1 ? K_OFF : V_OFF) + st * KV_BYTES) + g * KV_STRIDE + t * 8 + (32 * w + 16 * wg) * 2;
                PIN(mrd); PIN(dl);
                uint4 b[10];
                mbar_wait_u(sb + MB_M, st);
                TS(0);
#pragma unroll
                for (int i = 0; i < 3; i++) b[i] = lds128(mrd + i * 1024);
                mbar_wait_u(sb + MB_M + 8, st);
#pragma unroll
                for (int i = 3; i < 6; i++) b[i] = lds128(mrd + i * 1024);
                uint32_t chk = 0xffffffffu;
#pragma unroll
                for (int i = 0; i < 10; i++) {
                    if (i == 3) {
                        mbar_wait_u(sb + MB_M + 16, st);
#pragma unroll
                        for (int k = 6; k < 10; k++) b[k] = lds128(mrd + k * 1024);
                    }
                    mma16(acc[1][0], A[1][2 * i], b[i].x, b[i].y);
                    mma16(acc[1][1], A[1][2 * i + 1], b[i].z, b[i].w);
                    mma16(acc[0][0], A[0][2 * i], b[i].x, b[i].y);
                    mma16(acc[0][1], A[0][2 * i + 1], b[i].z, b[i].w);
                    chk = min(chk, min4(b[i]));
                }
                if (__any_sync(~0u, chk == 0)) {
                    mbar_wait_u(sb + MB_V, st);
#pragma unroll
                    for (int i = 0; i < 16; i++) ((float*)acc)[i] = 0.f;
#pragma unroll
                    for (int i = 0; i < 10; i++) {
                        const uint4 bb = lds128(mrd + i * 1024);
                        mma16(acc[1][0], A[1][2 * i], bb.x, bb.y);
                        mma16(acc[1][1], A[1][2 * i + 1], bb.z, bb.w);
                        mma16(acc[0][0], A[0][2 * i], bb.x, bb.y);
                        mma16(acc[0][1], A[0][2 * i + 1], bb.z, bb.w);
                    }
                }
                sts128f(sb + SCR_OFF + warp * 512 + l16, acc[1][0][0] + acc[1][1][0], acc[1][0][1] + acc[1][1][1],
                        acc[1][0][2] + acc[1][1][2], acc[1][0][3] + acc[1][1][3]);
                const float k0 = acc[0][0][0] + acc[0][1][0], k1 = acc[0][0][1] + acc[0][1][1];
                const float k2 = acc[0][0][2] + acc[0][1][2], k3 = acc[0][0][3] + acc[0][1][3];
                TS(1);
                bar_sync(2 + w, 64);
                const uint4 o = lds128(sb + SCR_OFF + (warp ^ 4) * 512 + l16);
                const uint32_t u0 = movm(pack2(k0 + __uint_as_float(o.x), k1 + __uint_as_float(o.y)));
                const uint32_t u1 = movm(pack2(k2 + __uint_as_float(o.z), k3 + __uint_as_float(o.w)));
#pragma unroll
                for (int r = 0; r < 3; r++) st_async8(mapa(dl, r), u0, u1, mapa(sb + MB_H1, r));
            }
            TS(2);
            if (s == NSEG_ - 1) break;
            FRESH_LANE();
            uint32_t wa[8][4];
            const bool pair = wg || (w >= 2 && rank != 2);
            const int tileA = wg ? 2 * w : (pair ? 6 + 2 * w : 8 + w);
            const uint32_t stg_hi = pair ? 32u : 64u * WO_STRIDE;
            if (wg) {
                const uint32_t wo_l = sb + WO_OFF + ((lane & 7) + (lane >> 4) * 8) * WO_STRIDE + ((lane >> 3) & 1) * 16;
#pragma unroll
                for (int ks = 0; ks < 8; ks++) ldsm4t(wa[ks], wo_l + tileA * 32 + (ks & 3) * 16 * WO_STRIDE + (ks >> 2) * stg_hi);
                if (w == 0 && s + 2 < NSEG_) {
                    mbar_wait_u(sb + MB_H1, st);
                    if (lane == 0) {
                        mbar_expect(sb + MB_X + 8 * st, 40960);
                        for (int kb = rank; kb < 10; kb += 3)
                            tma3d_mc(sb + XT_OFF + st * 40960 + kb * 4096, &tmx, 0, 32 * (s + 2), kb, sb + MB_X + 8 * st);
                    }
                    __syncwarp();
                }
            } else {
                const uint32_t r8 = (lane & 7) * KV_STRIDE;
                const int mt = w & 1, eh = w >> 1;
                mbar_wait_u(sb + MB_V, st);
                mbar_wait_u(sb + MB_KV + 8 * st, (s >> 1) & 1);
                {
                    const uint32_t kb_ = sb + K_OFF + st * KV_BYTES + eh * 128 + r8;
                    const uint32_t ka = kb_ + (8 + 16 * mt + ((lane >> 3) & 1) * 8) * KV_STRIDE + (lane >> 4) * 16;
                    const uint32_t qa = sb + QM_OFF + eh * 128 + r8 + (lane >> 3) * 16;
                    const uint32_t sw = sb + M_OFF + eh * 1280 + mt * 64 + t * 320 + g * 4;
                    const uint32_t sm = sb + M_OFF + 2560 + w * 256 + t * 64 + g * 4;
                    uint32_t a[4][4], b[2][4], am[4];
#pragma unroll
                    for (int k = 0; k < 4; k++) ldsm4(a[k], ka + k * 32);
                    const uint32_t kma = kb_ + mt * 64 + (lane >> 3) * 16;
                    PIN(qa); PIN(sw); PIN(sm); PIN(kma);
                    mbar_wait_u(sb + MB_H1, st);
                    TS(3);
                    ldsm4(b[0], qa); ldsm4(b[1], qa + 64);
                    ldsm4(am, kma);
                    float c0[4] = {0, 0, 0, 0}, c1[4] = {0, 0, 0, 0}, c2[4] = {0, 0, 0, 0}, c3[4] = {0, 0, 0, 0};
                    mma16(c0, a[0], b[0][0], b[0][1]); mma16(c1, a[1], b[0][2], b[0][3]);
                    mma16r(c2, am[0], 0u, am[1], 0u, mt ? b[1][0] : b[0][0], mt ? b[1][1] : b[0][1]);
                    mma16r(c3, am[2], 0u, am[3], 0u, mt ? b[1][2] : b[0][2], mt ? b[1][3] : b[0][3]);
                    mma16(c0, a[2], b[1][0], b[1][1]); mma16(c1, a[3], b[1][2], b[1][3]);
                    sts32f(sm, c2[0] + c3[0]); sts32f(sm + 32, c2[1] + c3[1]);
                    sts32f(sw, c0[0] + c1[0]); sts32f(sw + 160, c0[1] + c1[1]);
                    sts32f(sw + 32, c0[2] + c1[2]); sts32f(sw + 160 + 32, c0[3] + c1[3]);
                }
                uint32_t vb[2][2][4], vc[4];
                {
                    const uint32_t va = sb + V_OFF + st * KV_BYTES + w * 64 + r8;
                    const uint32_t va1 = va + ((lane >> 3) & 1) * 8 * KV_STRIDE + (lane >> 4) * 16;
                    ldsm4t(vb[0][0], va1); ldsm4t(vb[0][1], va1 + 32);
                    ldsm4t(vb[1][0], va1 + 16 * KV_STRIDE); ldsm4t(vb[1][1], va1 + 16 * KV_STRIDE + 32);
                    ldsm4t(vc, va + 32 * KV_STRIDE + (lane >> 3) * 16);
                }
                const uint32_t sr = sb + M_OFF + g * 160 + t * 8;
                bar_sync(7, 128);
                TS(4);
                float sc[10];
                {
                    float2 m[4], p0[4], p1[4];
#pragma unroll
                    for (int j = 0; j < 4; j++) { p0[j] = lds64f(sr + j * 32); p1[j] = lds64f(sr + 1280 + j * 32); }
#pragma unroll
                    for (int j = 0; j < 4; j++) m[j] = lds64f(sb + M_OFF + 2560 + j * 256 + lane * 8);
#pragma unroll
                    for (int j = 0; j < 4; j++) { sc[2 + 2 * j] = p0[j].x + p1[j].x; sc[3 + 2 * j] = p0[j].y + p1[j].y; }
                    sc[0] = (m[0].x + m[1].x) + (m[2].x + m[3].x); sc[1] = (m[0].y + m[1].y) + (m[2].y + m[3].y);
                }
                float mx = fmaxf(fmaxf(fmaxf(sc[2], sc[3]), fmaxf(sc[4], sc[5])), fmaxf(fmaxf(sc[6], sc[7]), fmaxf(sc[8], sc[9])));
                mx = fmaxf(mx, fmaxf(sc[0], sc[1]));
                mx = fmaxf(mx, __shfl_xor_sync(~0u, mx, 1)); mx = fmaxf(mx, __shfl_xor_sync(~0u, mx, 2));
                const float nm = -mx * (SCALE * LOG2E);
#pragma unroll
                for (int i = 0; i < 10; i++) sc[i] = ex2(fmaf(sc[i], SCALE * LOG2E, nm));
                uint32_t p[5];
#pragma unroll
                for (int j = 0; j < 5; j++) p[j] = pack2(sc[2 * j], sc[2 * j + 1]);
                float o[4][4];
#pragma unroll
                for (int i = 0; i < 16; i++) ((float*)o)[i] = 0.f;
#pragma unroll
                for (int n = 0; n < 4; n++) mma16r(o[n], p[0], 0u, p[1], 0u, vb[0][n >> 1][2 * (n & 1)], vb[0][n >> 1][2 * (n & 1) + 1]);
#pragma unroll
                for (int n = 0; n < 4; n++) mma16r(o[n], p[2], 0u, p[3], 0u, vb[1][n >> 1][2 * (n & 1)], vb[1][n >> 1][2 * (n & 1) + 1]);
#pragma unroll
                for (int n = 0; n < 4; n++) mma8(o[n], p[4], 0u, vc[n]);
                float sum = ((sc[0] + sc[1]) + (sc[2] + sc[3])) + ((sc[4] + sc[5]) + (sc[6] + sc[7])) + (sc[8] + sc[9]);
                sum += __shfl_xor_sync(~0u, sum, 1); sum += __shfl_xor_sync(~0u, sum, 2);
                const float inv = rcp(sum);
                sts128(sb + M_OFF + 4096 + w * 512 + l16,
                       make_uint4(pack2(o[0][0] * inv, o[0][1] * inv), pack2(o[1][0] * inv, o[1][1] * inv),
                                  pack2(o[2][0] * inv, o[2][1] * inv), pack2(o[3][0] * inv, o[3][1] * inv)));
                const uint32_t wo_l = sb + WO_OFF + ((lane & 7) + (lane >> 4) * 8) * WO_STRIDE + ((lane >> 3) & 1) * 16;
#pragma unroll
                for (int ks = 0; ks < 8; ks++) ldsm4t(wa[ks], wo_l + tileA * 32 + (ks & 3) * 16 * WO_STRIDE + (ks >> 2) * stg_hi);
            }
            const uint32_t wb = sb + WO_OFF + ((lane & 7) + (lane >> 4) * 8 + 64) * WO_STRIDE + ((lane >> 3) & 1) * 16 + tileA * 32;
            const uint32_t poff = ((t * 2 + (g >> 2)) * 128 + (g & 3)) * 2;
            uint2* pdst = (uint2*)&g_P[st][((int)rank * 7 + (tileA >> 1)) * 1024 + head * 4] + (tileA & 1) + poff;
            PIN(wb); PIN(poff);
            bar_sync(1, 256);
            if (lane == 0) mbar_arrive(sb + MB_WO);
            TS(5);
            if (pair) {
                float d[4][4];
#pragma unroll
                for (int i = 0; i < 16; i++) ((float*)d)[i] = 0.f;
#pragma unroll
                for (int hf = 0; hf < 2; hf++) {
                    const uint4 o0 = lds128(sb + M_OFF + 4096 + hf * 1024 + l16), o1 = lds128(sb + M_OFF + 4096 + hf * 1024 + 512 + l16);
                    mma16(d[0], wa[0], o0.x, o0.y); mma16(d[2], wa[4], o0.x, o0.y);
                    mma16(d[1], wa[1], o0.z, o0.w); mma16(d[3], wa[5], o0.z, o0.w);
                    if (hf == 0) { ldsm4t(wa[0], wb); ldsm4t(wa[4], wb + 32); ldsm4t(wa[1], wb + 16 * WO_STRIDE); ldsm4t(wa[5], wb + 16 * WO_STRIDE + 32); }
                    mma16(d[0], wa[2], o1.x, o1.y); mma16(d[2], wa[6], o1.x, o1.y);
                    mma16(d[1], wa[3], o1.z, o1.w); mma16(d[3], wa[7], o1.z, o1.w);
                    if (hf == 0) {
                        ldsm4t(wa[2], wb + 32 * WO_STRIDE); ldsm4t(wa[6], wb + 32 * WO_STRIDE + 32);
                        ldsm4t(wa[3], wb + 48 * WO_STRIDE); ldsm4t(wa[7], wb + 48 * WO_STRIDE + 32);
                    }
                }
                st_rel16(pdst, make_uint4(nzw(pack2(d[0][0] + d[1][0], d[0][1] + d[1][1])), nzw(pack2(d[0][2] + d[1][2], d[0][3] + d[1][3])),
                                          nzw(pack2(d[2][0] + d[3][0], d[2][1] + d[3][1])), nzw(pack2(d[2][2] + d[3][2], d[2][3] + d[3][3]))));
            } else {
                float d[2][4];
#pragma unroll
                for (int i = 0; i < 8; i++) ((float*)d)[i] = 0.f;
#pragma unroll
                for (int k = 0; k < 4; k++) {
                    const uint4 o0 = lds128(sb + M_OFF + 4096 + k * 512 + l16);
                    mma16(d[0], wa[2 * k], o0.x, o0.y); mma16(d[1], wa[2 * k + 1], o0.z, o0.w);
                }
                st_rel8(pdst, nzw(pack2(d[0][0] + d[1][0], d[0][1] + d[1][1])), nzw(pack2(d[0][2] + d[1][2], d[0][3] + d[1][3])));
            }
            fence_async_smem();
            __syncwarp();
            if (lane < 3) asm volatile("mbarrier.arrive.relaxed.cluster.shared::cluster.b64 _, [%0];" ::"r"(mapa(sb + MB_WD, lane)) : "memory");
            TS(6);
            TSV(14, threadIdx.x == 224, clk());
            xproj(s + 1);
            TS(7);
        }
    } else {
      asm volatile("setmaxnreg.dec.sync.aligned.u32 56;");
      if (warp < 11) {
        const int cw = warp - 8, ct = cw * 32 + lane;
        const int unit = blockIdx.x + 96 * cw;
        const bool isred = unit < 160;
        const int ukp = unit >> 3, utq = (unit >> 1) & 3, ugh = unit & 1;
        const int umpos = (ukp % 10) * 2 + ukp / 10;
        const int mword = (umpos * 32 + utq * 8 + ((lane >> 2) & 1) * 4 + ugh * 2 + ((lane >> 1) & 1)) * 4 + ((lane >> 4) & 1) * 2 + ((lane >> 3) & 1);
        const uint32_t gbytes = cw == 2 ? 4096 : 3072;
        if (isred && !(lane & 1)) st_rel4((uint32_t*)g_M[3] + mword, 0);
        {
            const int nch = rank == 2 ? 24 : 28;
            for (int r = cw; r < 128; r += 3) {
                if (lane < nch) cp_async16(sb + WO_OFF + r * WO_STRIDE + lane * 16, Wo + (size_t)(head * 128 + eperm(r)) * DM_ + rank * 224 + lane * 8);
            }
            asm volatile("cp.async.commit_group;" ::: "memory");
#pragma unroll 1
            for (int p = ct; p < 640; p += 96) {
                const int mpos = p >> 5, l = p & 31;
                const int kp = (mpos & 1) * 10 + (mpos >> 1);
                const uint32_t* mp = (const uint32_t*)(mem0 + (l >> 2) * DM_ + kp * 32 + 2 * (l & 3));
                uint4 v; v.x = nzw(__ldg(mp)); v.y = nzw(__ldg(mp + 4)); v.z = nzw(__ldg(mp + 8)); v.w = nzw(__ldg(mp + 12));
                sts128(sb + M_OFF + p * 16, v);
            }
            asm volatile("cp.async.wait_all;" ::: "memory");
            __threadfence();
            bar_sync(6, 96);
            if (lane == 0) { mbar_arrive(sb + MB_M + 8 * cw); mbar_arrive(sb + MB_V); mbar_expect(sb + MB_M + 8 * cw, gbytes); }
        }
        int rpar = 0;
#pragma unroll 1
        for (int s = 0; s < NSEG_ - 1; s++) {
            int lane_o = lane, mword_o = mword;
            asm volatile("" : "+r"(lane_o), "+r"(mword_o));
            uint4* psrc = &g_P[s & 1][unit * 128 + lane_o];
            uint32_t* mdst = (uint32_t*)g_M[(s + 1) & 3] + mword_o;
            mbar_wait_u(sb + MB_WO, s & 1);
            const int tw = clk();
            TS(10);
            if (isred) {
                while (clk() - tw < DELAY_P) {}
                uint4 v[4];
                int guard = 0;
#pragma unroll
                for (int j = 0; j < 4; j++) v[j] = ld_poll16(psrc + j * 32);
                while (__any_sync(~0u, min(min(min4(v[0]), min4(v[1])), min(min4(v[2]), min4(v[3]))) == 0)) {
                    if (++guard > SPIN_LIMIT) { g_misc[2] = 2; break; }
                    { const int tb = clk(); while (clk() - tb < BACKOFF) {} }
#pragma unroll
                    for (int j = 0; j < 4; j++) if (min4(v[j]) == 0) v[j] = ld_poll16(psrc + j * 32);
                }
                __syncwarp();
                TS(11);
                float a[8];
                a[0] = (bflo(v[0].x) + bflo(v[1].x)) + (bflo(v[2].x) + bflo(v[3].x)); a[1] = (bfhi(v[0].x) + bfhi(v[1].x)) + (bfhi(v[2].x) + bfhi(v[3].x));
                a[2] = (bflo(v[0].y) + bflo(v[1].y)) + (bflo(v[2].y) + bflo(v[3].y)); a[3] = (bfhi(v[0].y) + bfhi(v[1].y)) + (bfhi(v[2].y) + bfhi(v[3].y));
                a[4] = (bflo(v[0].z) + bflo(v[1].z)) + (bflo(v[2].z) + bflo(v[3].z)); a[5] = (bfhi(v[0].z) + bfhi(v[1].z)) + (bfhi(v[2].z) + bfhi(v[3].z));
                a[6] = (bflo(v[0].w) + bflo(v[1].w)) + (bflo(v[2].w) + bflo(v[3].w)); a[7] = (bfhi(v[0].w) + bfhi(v[1].w)) + (bfhi(v[2].w) + bfhi(v[3].w));
                __syncwarp();
                const bool b4 = lane & 16, b3 = lane & 8, b2 = lane & 4;
                float c[4], d[2], e;
#pragma unroll
                for (int i = 0; i < 4; i++) c[i] = (b4 ? a[i + 4] : a[i]) + __shfl_xor_sync(~0u, b4 ? a[i] : a[i + 4], 16);
#pragma unroll
                for (int i = 0; i < 2; i++) d[i] = (b3 ? c[i + 2] : c[i]) + __shfl_xor_sync(~0u, b3 ? c[i] : c[i + 2], 8);
                e = (b2 ? d[1] : d[0]) + __shfl_xor_sync(~0u, b2 ? d[0] : d[1], 4);
                const float f = __shfl_xor_sync(~0u, e, 1);
                if (!(lane & 1)) st_rel4(mdst, nzw(pack2(e, f)));
                TS(12);
            }
            if (cw == 0) {
                const int tb = clk();
                mbar_wait_u(sb + MB_WD, s & 1);
                while (clk() - tb < DELAY_M) {}
                if (lane == 0)
                    asm volatile("cp.async.bulk.shared::cluster.global.mbarrier::complete_tx::bytes.multicast::cluster [%0], [%1], %2, [%3], %4;"
                                 ::"r"(sb + M_OFF + rank * 3072), "l"(&g_M[(s + 1) & 3][rank * 192]), "r"(rank == 2 ? 4096 : 3072),
                                   "r"(sb + MB_M + 8 * rank), "h"((uint16_t)7) : "memory");
                __syncwarp();
            }
            {
                mbar_wait_u(sb + MB_M + 8 * cw, (s + 1) & 1);
                const uint32_t mr = sb + M_OFF + cw * 3072 + lane_o * 16;
                int guard = 0;
                while (true) {
                    uint32_t chk = 0xffffffffu;
#pragma unroll
                    for (int j = 0; j < 6; j++) chk = min(chk, min4(lds128(mr + j * 512)));
                    if (cw == 2) chk = min(chk, min(min4(lds128(mr + 3072)), min4(lds128(mr + 3584))));
                    if (!__any_sync(~0u, chk == 0)) break;
                    if (++guard > SPIN_LIMIT) { g_misc[2] = 3; break; }
                    { const int tb = clk(); while (clk() - tb < BACKOFF) {} }
                    if (lane == 0) {
                        mbar_expect(sb + MB_R + 8 * cw, gbytes);
                        bulk_g2s(sb + M_OFF + cw * 3072, &g_M[(s + 1) & 3][cw * 192], gbytes, sb + MB_R + 8 * cw);
                    }
                    __syncwarp();
                    mbar_wait_u(sb + MB_R + 8 * cw, rpar); rpar ^= 1;
                }
                if (lane == 0) { mbar_arrive(sb + MB_V); mbar_expect(sb + MB_M + 8 * cw, gbytes); }
                TS(13);
                TSV(15, threadIdx.x == 256, guard);
            }
            if (isred) {
#pragma unroll
                for (int j = 0; j < 4; j++) st_rel16(psrc + j * 32, make_uint4(0, 0, 0, 0));
                if (s > 0 && !(lane & 1)) st_rel4((uint32_t*)g_M[s & 3] + mword_o, 0);
                __threadfence();
            }
        }
      } else {
        unsigned* cnt = &g_oxcnt[head < 20 ? head / 5 : 4 + (head - 20) / 4];
#pragma unroll 1
        for (int task = rank; task < 2 * NSEG_; task += 3) {
            const int s = task >> 1, mt = task & 1;
            const int st = s & 1;
            mbar_wait_u(sb + MB_KV + 8 * st, (s >> 1) & 1);
            mbar_wait_u(sb + MB_H1, st);
            TS(8);
            float sc[5][4];
#pragma unroll
            for (int i = 0; i < 20; i++) ((float*)sc)[i] = 0.f;
            const uint32_t r8 = (lane & 7) * KV_STRIDE;
            {
                const uint32_t qa = sb + QX_OFF + st * QX_BYTES + (16 * mt + ((lane >> 3) & 1) * 8) * KV_STRIDE + r8 + (lane >> 4) * 16;
                const uint32_t ka = sb + K_OFF + st * KV_BYTES + r8 + ((lane >> 3) & 1) * 16;
#pragma unroll 2
                for (int ks = 0; ks < 8; ks++) {
                    uint32_t a[4], b0[4], b1[4], b2[2];
                    ldsm4(a, qa + ks * 32);
                    ldsm4(b0, ka + (lane >> 4) * 8 * KV_STRIDE + ks * 32);
                    ldsm4(b1, ka + (16 + (lane >> 4) * 8) * KV_STRIDE + ks * 32);
                    ldsm2(b2, ka + 32 * KV_STRIDE + ks * 32);
                    mma16(sc[0], a, b0[0], b0[1]); mma16(sc[1], a, b0[2], b0[3]);
                    mma16(sc[2], a, b1[0], b1[1]); mma16(sc[3], a, b1[2], b1[3]);
                    mma16(sc[4], a, b2[0], b2[1]);
                }
            }
            uint32_t p[5][2];
#pragma unroll
            for (int h = 0; h < 2; h++) {
                const int lim = 8 + 16 * mt + g + 8 * h - 2 * t;
                float mx = -3.0e38f;
#pragma unroll
                for (int j = 0; j < 5; j++) {
                    uint32_t r1 = pack2(sc[j][2 * h], sc[j][2 * h + 1]);
                    r1 = pack2(bflo(r1) * SCALE, bfhi(r1) * SCALE);
                    const float v0 = (8 * j <= lim) ? bflo(r1) : -1.0e9f, v1 = (8 * j + 1 <= lim) ? bfhi(r1) : -1.0e9f;
                    sc[j][2 * h] = v0; sc[j][2 * h + 1] = v1; mx = fmaxf(mx, fmaxf(v0, v1));
                }
                mx = fmaxf(mx, __shfl_xor_sync(~0u, mx, 1)); mx = fmaxf(mx, __shfl_xor_sync(~0u, mx, 2));
                float sum = 0.f;
#pragma unroll
                for (int j = 0; j < 5; j++) {
#pragma unroll
                    for (int i = 0; i < 2; i++) { float e = ex2((sc[j][2 * h + i] - mx) * LOG2E); sc[j][2 * h + i] = e; sum += e; }
                }
                sum += __shfl_xor_sync(~0u, sum, 1); sum += __shfl_xor_sync(~0u, sum, 2);
                const float inv = rcp(sum);
#pragma unroll
                for (int j = 0; j < 5; j++) p[j][h] = pack2(sc[j][2 * h] * inv, sc[j][2 * h + 1] * inv);
            }
            uint32_t* og = (uint32_t*)(g_ox + (size_t)(s * NH_ + head) * 512) + (16 * mt + g) * 32 + t;
            const uint32_t va = sb + V_OFF + st * KV_BYTES + r8;
#pragma unroll 2
            for (int np = 0; np < 8; np++) {
                uint32_t b0[4], b1[4], b2[2];
                ldsm4t(b0, va + ((lane >> 3) & 1) * 8 * KV_STRIDE + (lane >> 4) * 16 + np * 32);
                ldsm4t(b1, va + (16 + ((lane >> 3) & 1) * 8) * KV_STRIDE + (lane >> 4) * 16 + np * 32);
                ldsm2t(b2, va + 32 * KV_STRIDE + ((lane >> 3) & 1) * 16 + np * 32);
#pragma unroll
                for (int n = 0; n < 2; n++) {
                    float o[4] = {0, 0, 0, 0};
                    mma16r(o, p[0][0], p[0][1], p[1][0], p[1][1], b0[2 * n], b0[2 * n + 1]);
                    mma16r(o, p[2][0], p[2][1], p[3][0], p[3][1], b1[2 * n], b1[2 * n + 1]);
                    mma8(o, p[4][0], p[4][1], b2[n]);
                    const int ch = (2 * np + n) & 7;
                    uint32_t* o2 = og + (np >> 2) * 1024 + ((ch ^ g) << 2);
                    o2[0] = pack2(o[0], o[1]);
                    o2[256] = pack2(o[2], o[3]);
                }
            }
            __syncwarp();
            if (lane < 3) asm volatile("mbarrier.arrive.relaxed.cluster.shared::cluster.b64 _, [%0];" ::"r"(mapa(sb + MB_FREE + 8 * st, lane)) : "memory");
            if (lane == 0) red_rel(cnt + s * 8, 1);
            __syncwarp();
            TS(9);
        }
      }
    }
    __syncthreads();
    CAL(blockIdx.x, 1);
    cluster_sync();
}

constexpr int U_STRIDE = 136 * 48;
constexpr int KR_STRIDE = 2080 * 2 * 2;
constexpr int B_U_OFF = 0, B_KR_OFF = 8 * U_STRIDE, B_CONV_END = B_KR_OFF + 8 * KR_STRIDE;
constexpr int B_OX_STAGES = 3, B_OX_BYTES = 40960;
constexpr int B_BAR_OFF = B_OX_STAGES * B_OX_BYTES;
constexpr int B_SMEM = B_BAR_OFF + 128;

constexpr int B_THREADS = 384;
constexpr int B_LAG = 2;

__global__ void __launch_bounds__(B_THREADS, 1)
aux_kernel(const bf16* __restrict__ x, const bf16* __restrict__ Wo, const bf16* __restrict__ Bk, const bf16* __restrict__ Bv,
           const bf16* __restrict__ shk, const bf16* __restrict__ ssmk, const bf16* __restrict__ ssmD,
           const bf16* __restrict__ gatew, bf16* __restrict__ out) {
    extern __shared__ __align__(1024) unsigned char smem[];
    __shared__ unsigned s_flag;
    const uint32_t sb = __shfl_sync(0xffffffffu, smem_u32(smem), 0);
    const int tid = threadIdx.x, lane = tid & 31, warp = __shfl_sync(0xffffffffu, tid >> 5, 0);
    const int g = lane >> 2, t = lane & 3;
    const int cta = blockIdx.x;
    const int kg = cta / NCR_, cr = cta % NCR_;
    const int h0 = kg < 4 ? kg * 5 : 20 + (kg - 4) * 4, nh = kg < 4 ? 5 : 4;
    const uint32_t mb_full = sb + B_BAR_OFF, mb_empty = mb_full + 24, mb_st = mb_full + 48, mb_go = mb_full + 80;
    if (tid == 0) {
        for (int i = 0; i < B_OX_STAGES; i++) { mbar_init(mb_full + 8 * i, 1); mbar_init(mb_empty + 8 * i, 8); }
        for (int i = 0; i < 4; i++) mbar_init(mb_st + 8 * i, 8);
        mbar_init(mb_go, 8);
        fence_async_smem();
    }
    __syncthreads();
    if (warp >= 8) {
      asm volatile("setmaxnreg.dec.sync.aligned.u32 40;");
      if (warp == 8) {
        if (lane == 0) {
            { int guard = 0; while (!mbar_try(mb_go, 0)) { if (++guard > (1 << 22)) break; } }
            for (int n = 0; n < NSEG_; n++) {
                const int st = n % B_OX_STAGES;
                if (n >= B_OX_STAGES) mbar_wait(mb_empty + 8 * st, (n / B_OX_STAGES - 1) & 1);
                int guard = 0;
                while (ld_acq(&g_oxcnt[n * 8 + kg]) < (unsigned)(2 * nh)) { if (SPIN_FAIL(guard, 4)) break; __nanosleep(200); }
                fence_async_all();
                mbar_expect(mb_full + 8 * st, nh * 8192);
                bulk_g2s(sb + st * B_OX_BYTES, g_ox + (size_t)(n * NH_ + h0) * 512, nh * 8192, mb_full + 8 * st);
            }
        }
      } else if (warp == 9) {
        if (lane == 0) {
            { int guard = 0; while (!mbar_try(mb_go, 0)) { if (++guard > (1 << 22)) break; } }
            red_rel(&g_misc[0], 1);
            for (int n = 0; n < NSEG_; n++) {
                { int guard = 0; while (!mbar_try(mb_st + 8 * (n & 3), (n >> 2) & 1)) { if (++guard > (1 << 20)) break; } }
                red_rel(&g_pcnt[n * 8 + cr], 1);
            }
        }
      }
    } else {
    asm volatile("setmaxnreg.inc.sync.aligned.u32 232;");
    CAL(96 + cta, 0);
    for (int r = cta * 8 + warp; r < S_; r += NB_CTAS * 8) {
        float acc = 0.f;
#pragma unroll
        for (int i = 0; i < 10; i++) {
            uint32_t xv = __ldg((const uint32_t*)(x + (size_t)r * DM_) + lane + 32 * i), wv = __ldg((const uint32_t*)gatew + lane + 32 * i);
            acc += rbf(bflo(xv) * bflo(wv)) + rbf(bfhi(xv) * bfhi(wv));
        }
#pragma unroll
        for (int o = 16; o; o >>= 1) acc += __shfl_xor_sync(~0u, acc, o);
        if (lane == 0) g_gate[r] = rbf(1.f / (1.f + __expf(-rbf(acc))));
    }

    for (int item = cta; item < 80; item += NB_CTAS) {
        const int c0 = item * 8;
        bar_sync(1, 256);
        for (int i = tid; i < 8 * 24; i += 256) sts128(sb + B_U_OFF + (i / 24) * U_STRIDE + (i % 24) * 16, make_uint4(0, 0, 0, 0));
        {
            bf16* kr = (bf16*)(smem + B_KR_OFF + warp * KR_STRIDE);
            const bf16* kp = ssmk + (size_t)(c0 + warp) * S_;
            for (int i = lane; i < 256; i += 32) {
                uint4 v = __ldg((const uint4*)kp + i);
                const bf16* e = (const bf16*)&v;
#pragma unroll
                for (int j = 0; j < 8; j++) { int idx = 2047 - (8 * i + j); kr[idx] = e[j]; if (idx > 0) kr[2080 + idx - 1] = e[j]; }
            }
            kr[2048 + lane] = __float2bfloat16(0.f); kr[2080 + 2047 + lane] = __float2bfloat16(0.f);
            if (lane == 0) kr[2080 + 2079] = __float2bfloat16(0.f);
        }
        {
            float sh[8][4];
#pragma unroll
            for (int c = 0; c < 8; c++) {
                uint2 v = __ldg((const uint2*)(shk + (c0 + c) * 4));
                sh[c][0] = bflo(v.x); sh[c][1] = bfhi(v.x); sh[c][2] = bflo(v.y); sh[c][3] = bfhi(v.y);
            }
            const int t0 = tid * 8;
            uint4 kr[11], vr[8];
#pragma unroll
            for (int i = 0; i < 11; i++) { int r = t0 - 3 + i; kr[i] = r >= 0 ? __ldg((const uint4*)(Bk + (size_t)r * DM_ + c0)) : make_uint4(0, 0, 0, 0); }
#pragma unroll
            for (int i = 0; i < 8; i++) vr[i] = __ldg((const uint4*)(Bv + (size_t)(t0 + i) * DM_ + c0));
#pragma unroll
            for (int c = 0; c < 8; c++) {
                float res[8];
#pragma unroll
                for (int i = 0; i < 8; i++) {
                    float a = 0.f;
#pragma unroll
                    for (int tt = 0; tt < 4; tt++) {
                        uint32_t wd = ((const uint32_t*)&kr[i + tt])[c >> 1];
                        float kv_ = (c & 1) ? bfhi(wd) : bflo(wd);
                        a = rbf(a + rbf(kv_ * sh[c][3 - tt]));
                    }
                    uint32_t wd = ((const uint32_t*)&vr[i])[c >> 1];
                    res[i] = a * ((c & 1) ? bfhi(wd) : bflo(wd));
                }
                uint4 o = make_uint4(pack2(res[0], res[1]), pack2(res[2], res[3]), pack2(res[4], res[5]), pack2(res[6], res[7]));
                sts128(sb + B_U_OFF + c * U_STRIDE + (8 + (tid >> 1)) * 48 + (tid & 1) * 16, o);
            }
        }
        bar_sync(1, 256);
        {
            float acc[16][4];
#pragma unroll
            for (int i = 0; i < 64; i++) ((float*)acc)[i] = 0.f;
            const uint32_t kb = sb + B_KR_OFF + warp * KR_STRIDE + ((g & 1) ? (2047 - g + 2 * t) * 2 : 4160 + (2046 - g + 2 * t) * 2);
            const uint32_t ub = sb + B_U_OFF + warp * U_STRIDE + (8 + (lane & 7) + (lane >> 4) * 8) * 48 + ((lane >> 3) & 1) * 16;
#pragma unroll 1
            for (int r = 0; r < 8; r++) {
                uint32_t pa[16][3];
#pragma unroll
                for (int m = 0; m < 16; m++) {
                    const uint32_t a = kb - (16 * (r + 8 * m)) * 2;
                    pa[m][0] = lds32(a + 16); pa[m][1] = lds32(a); pa[m][2] = lds32(a - 16);
                }
#pragma unroll
                for (int d = 0; d < 16; d += 2) {
                    uint32_t b[4];
                    ldsm4(b, ub + (8 * d - r) * 48);
#pragma unroll
                    for (int m = 0; m < 16 - d; m++) mma16r(acc[m + d], pa[m][1], pa[m][2], pa[m][0], pa[m][1], b[0], b[1]);
#pragma unroll
                    for (int m = 0; m < 15 - d; m++) mma16r(acc[m + d + 1], pa[m][1], pa[m][2], pa[m][0], pa[m][1], b[2], b[3]);
                }
            }
            __syncwarp();
            const float Dv = __bfloat162float(ssmD[c0 + warp]);
            bf16* u = (bf16*)(smem + B_U_OFF + warp * U_STRIDE) + 8 * 24;
#pragma unroll
            for (int i = 0; i < 16; i++) {
#pragma unroll
                for (int q = 0; q < 4; q++) {
                    const int idx = (8 * i + 2 * t + (q & 1)) * 24 + g + (q >> 1) * 8;
                    const float kvv = __bfloat162float(u[idx]);
                    u[idx] = __float2bfloat16_rn(rbf(acc[i][q]) + rbf(kvv * Dv));
                }
            }
        }
        bar_sync(1, 256);
        for (int r = tid; r < S_; r += 256) {
            uint4 xv = __ldg((const uint4*)(x + (size_t)r * DM_ + c0));
            uint32_t o[4];
            const bf16* u = (const bf16*)(smem + B_U_OFF) + (8 + (r >> 4)) * 24 + (r & 15);
#pragma unroll
            for (int c = 0; c < 4; c++) {
                uint32_t wd = ((const uint32_t*)&xv)[c];
                o[c] = pack2(bflo(wd) * __bfloat162float(u[(2 * c) * (U_STRIDE / 2)]), bfhi(wd) * __bfloat162float(u[(2 * c + 1) * (U_STRIDE / 2)]));
            }
            *(uint4*)(g_b + (size_t)r * DM_ + c0) = make_uint4(o[0], o[1], o[2], o[3]);
        }
    }
    fence_async_smem();
    __syncwarp();
    if (lane == 0) mbar_arrive(mb_go);
    CAL(96 + cta, 1);

    const int wg = warp >> 2, w = warp & 3;
    const int col = cr * 128 + wg * 64 + 16 * w + 2 * g;
    uint32_t A[40][4];
#pragma unroll
    for (int ks = 0; ks < 40; ks++) {
        const int hh = ks >> 3;
        uint32_t r[4] = {0, 0, 0, 0};
        if (hh < nh) {
#pragma unroll
            for (int i = 0; i < 4; i++) {
                const int p = (ks & 7) * 16 + 2 * t + (i & 1) + (i >> 1) * 8;
                r[i] = __ldg((const uint32_t*)(Wo + (size_t)((h0 + hh) * 128 + eperm(p)) * DM_ + col));
            }
        }
        A[ks][0] = __byte_perm(r[0], r[1], 0x5410); A[ks][1] = __byte_perm(r[0], r[1], 0x7632);
        A[ks][2] = __byte_perm(r[2], r[3], 0x5410); A[ks][3] = __byte_perm(r[2], r[3], 0x7632);
    }
    CAL(96 + cta, 2);
    auto finalize = [&](int n) {
        const int r = kg + 7 * warp;
        if (r < 32) {
            if (lane == 0) {
                int guard = 0;
                while (ld_acq(&g_pcnt[n * 8 + cr]) < (unsigned)NKG_) { if (SPIN_FAIL(guard, 6)) break; __nanosleep(50); }
                if (n == 0) { guard = 0; while (ld_acq(&g_misc[0]) < (unsigned)NB_CTAS) { if (++guard > (1 << 22)) break; __nanosleep(200); } }
            }
            __syncwarp();
            const int row = n * 32 + r, c = cr * 128 + lane * 4;
            float4 v[NKG_];
#pragma unroll
            for (int k = 0; k < NKG_; k++) v[k] = __ldcg((const float4*)(g_part + ((size_t)k * S_ + row) * DM_ + c));
            const float gt = __ldcg(&g_gate[row]), og = rbf(1.f - gt);
            const uint2 bv = __ldcg((const uint2*)(g_b + (size_t)row * DM_ + c));
            float4 a = v[0];
#pragma unroll
            for (int k = 1; k < NKG_; k++) { a.x += v[k].x; a.y += v[k].y; a.z += v[k].z; a.w += v[k].w; }
            uint2 o;
            o.x = pack2(rbf(gt * rbf(a.x)) + rbf(og * bflo(bv.x)), rbf(gt * rbf(a.y)) + rbf(og * bfhi(bv.x)));
            o.y = pack2(rbf(gt * rbf(a.z)) + rbf(og * bflo(bv.y)), rbf(gt * rbf(a.w)) + rbf(og * bfhi(bv.y)));
            *(uint2*)(out + (size_t)row * DM_ + c) = o;
        }
    };
#pragma unroll 1
    for (int n = 0; n < NSEG_; n++) {
        const int st = n % B_OX_STAGES;
        { int guard = 0; while (!mbar_try(mb_full + 8 * st, (n / B_OX_STAGES) & 1)) { if (++guard > (1 << 20)) break; } }
        __syncwarp();
        float acc[16];
        const uint32_t d0 = __shfl_sync(0xffffffffu, desc_sw128(sb + st * B_OX_BYTES), 0);
        WG_FENCE();
#pragma unroll
        for (int ks = 0; ks < 32; ks++) wgmma_n32(acc, A[ks], d0 + (((ks >> 2) * 4096 + (ks & 3) * 32) >> 4), ks > 0);
        if (nh == 5) {
#pragma unroll
            for (int ks = 32; ks < 40; ks++) wgmma_n32(acc, A[ks], d0 + (((ks >> 2) * 4096 + (ks & 3) * 32) >> 4), 1);
        }
        WG_COMMIT();
        WG_WAIT0();
        if (lane == 0) mbar_arrive(mb_empty + 8 * st);
        float* pp = g_part + ((size_t)kg * S_ + n * 32) * DM_ + col;
#pragma unroll
        for (int j = 0; j < 4; j++) {
            *(float2*)(pp + (size_t)(8 * j + 2 * t) * DM_) = make_float2(acc[4 * j], acc[4 * j + 2]);
            *(float2*)(pp + (size_t)(8 * j + 2 * t + 1) * DM_) = make_float2(acc[4 * j + 1], acc[4 * j + 3]);
        }
        __syncwarp();
        if (lane == 0) mbar_arrive(mb_st + 8 * (n & 3));
        if (n >= B_LAG) finalize(n - B_LAG);
    }
    for (int n = NSEG_ - B_LAG; n < NSEG_; n++) finalize(n);
    CAL(96 + cta, 3);
    }
    __syncthreads();
    if (tid == 0) {
        unsigned old; asm volatile("atom.acq_rel.gpu.global.add.u32 %0, [%1], 1;" : "=r"(old) : "l"(&g_misc[1]) : "memory");
        s_flag = (old == NB_CTAS - 1);
    }
    __syncthreads();
    if (s_flag) {
        for (int i = tid; i < NSEG_ * 8; i += B_THREADS) { g_oxcnt[i] = 0; g_pcnt[i] = 0; }
        if (tid == 0) { g_misc[0] = 0; g_misc[1] = 0; }
    }
}

typedef CUresult (*EncodeFn)(CUtensorMap*, CUtensorMapDataType, cuuint32_t, void*, const cuuint64_t*, const cuuint64_t*,
                             const cuuint32_t*, const cuuint32_t*, CUtensorMapInterleave, CUtensorMapSwizzle,
                             CUtensorMapL2promotion, CUtensorMapFloatOOBfill);

extern "C" void kernel_launch(void* const* d_in, const int* in_sizes, int n_in, void* d_out, int out_size) {
    const bf16* x = (const bf16*)d_in[0];
    const bf16* mem0 = (const bf16*)d_in[1];
    const bf16* Wq = (const bf16*)d_in[2];
    const bf16* Wk = (const bf16*)d_in[3];
    const bf16* Wv = (const bf16*)d_in[4];
    const bf16* Wo = (const bf16*)d_in[5];
    const bf16* Bk = (const bf16*)d_in[8];
    const bf16* Bv = (const bf16*)d_in[9];
    const bf16* shk = (const bf16*)d_in[10];
    const bf16* ssmk = (const bf16*)d_in[11];
    const bf16* ssmD = (const bf16*)d_in[12];
    const bf16* gatew = (const bf16*)d_in[13];

    static EncodeFn enc = nullptr;
    if (!enc) {
        void* fn = nullptr; cudaDriverEntryPointQueryResult qr;
        cudaGetDriverEntryPoint("cuTensorMapEncodeTiled", &fn, cudaEnableDefault, &qr);
        enc = (EncodeFn)fn;
        cudaFuncSetAttribute(rec_kernel, cudaFuncAttributeMaxDynamicSharedMemorySize, A_SMEM + 1024);
        cudaFuncSetAttribute(aux_kernel, cudaFuncAttributeMaxDynamicSharedMemorySize, B_SMEM);
    }
    CUtensorMap tmx;
    {
        cuuint64_t dims[3] = {64, (cuuint64_t)S_, 10};
        cuuint64_t strides[2] = {DM_ * 2, 128};
        cuuint32_t box[3] = {64, 32, 1}, es[3] = {1, 1, 1};
        enc(&tmx, CU_TENSOR_MAP_DATA_TYPE_BFLOAT16, 3, (void*)x, dims, strides, box, es, CU_TENSOR_MAP_INTERLEAVE_NONE,
            CU_TENSOR_MAP_SWIZZLE_128B, CU_TENSOR_MAP_L2_PROMOTION_L2_256B, CU_TENSOR_MAP_FLOAT_OOB_FILL_NONE);
    }
    cudaStream_t st = cudaStreamPerThread;
    rec_kernel<<<96, A_THREADS, A_SMEM + 1024, st>>>(tmx, mem0, Wq, Wk, Wv, Wo);
    cudaLaunchConfig_t cfg = {};
    cfg.gridDim = dim3(NB_CTAS); cfg.blockDim = dim3(B_THREADS); cfg.dynamicSmemBytes = B_SMEM; cfg.stream = st;
    cudaLaunchAttribute at[1];
    at[0].id = cudaLaunchAttributeProgrammaticStreamSerialization; at[0].val.programmaticStreamSerializationAllowed = 1;
    cfg.attrs = at; cfg.numAttrs = 1;
    cudaLaunchKernelEx(&cfg, aux_kernel, x, Wo, Bk, Bv, shk, ssmk, ssmD, gatew, (bf16*)d_out);
}
```

```cpp
#include <cuda_runtime.h>
#include <cuda_bf16.h>
#include <cuda.h>
#include <stdint.h>
#include <type_traits>

typedef __nv_bfloat16 bf16;

constexpr int S_ = 2048, DM_ = 640, NH_ = 32, NSEG_ = 64;
constexpr int NKG_ = 7, NCR_ = 5, NB_CTAS = NKG_ * NCR_;

#define STAGGER 150
#define DELAY_X 250
#define DELAY_P 800
#define DELAY_M 800
#define BACKOFF 100
#define WGB 20
#define WGD 1
#define SPIN_LIMIT (1 << 13)
#define SPIN_FAIL(guard, code) (((++guard) & 1023) == 0 && (guard >= SPIN_LIMIT || *(volatile unsigned*)&g_misc[2] != 0) && ((g_misc[2] = (code)), true))

__device__ uint2 g_X[4][40 * 7 * 32];
__device__ uint4 g_ox[(size_t)NSEG_ * NH_ * 512];
__device__ float g_part[(size_t)NKG_ * S_ * DM_];
__device__ bf16 g_b[(size_t)S_ * DM_];
__device__ float g_gate[S_];
__device__ unsigned g_oxcnt[NSEG_ * 8];
__device__ unsigned g_pcnt[NSEG_ * 8];
__device__ unsigned g_misc[4];
#define CAL(b, i) do {} while (0)

__device__ __forceinline__ uint32_t smem_u32(const void* p) { return (uint32_t)__cvta_generic_to_shared(p); }
__device__ __forceinline__ void mbar_init(uint32_t mb, int cnt) { asm volatile("mbarrier.init.shared.b64 [%0], %1;" ::"r"(mb), "r"(cnt)); }
__device__ __forceinline__ void mbar_expect(uint32_t mb, int bytes) { asm volatile("mbarrier.arrive.expect_tx.shared.b64 _, [%0], %1;" ::"r"(mb), "r"(bytes) : "memory"); }
__device__ __forceinline__ void mbar_arrive(uint32_t mb) { asm volatile("mbarrier.arrive.shared.b64 _, [%0];" ::"r"(mb) : "memory"); }
__device__ __forceinline__ bool mbar_try(uint32_t mb, int parity) {
    uint32_t ok;
    asm volatile("{ .reg .pred p; mbarrier.try_wait.parity.shared.b64 p, [%1], %2; selp.u32 %0, 1, 0, p; }" : "=r"(ok) : "r"(mb), "r"(parity) : "memory");
    return ok;
}
__device__ __forceinline__ void mbar_wait(uint32_t mb, int parity) {
    int guard = 0;
    while (!mbar_try(mb, parity)) { if (SPIN_FAIL(guard, 1)) break; }
}
__device__ __forceinline__ void mbar_wait_u(uint32_t mb, int parity) {
    asm volatile("{ .reg .pred p; .reg .u32 c; mov.u32 c, 0;\n"
                 "WL%=: mbarrier.try_wait.parity.shared.b64 p, [%0], %1;\n"
                 "@p bra.uni WD%=;\n"
                 "add.u32 c, c, 1; setp.lt.u32 p, c, 16384;\n"
                 "@p bra.uni WL%=;\n"
                 "WD%=: }" ::"r"(mb), "r"(parity) : "memory");
}
__device__ __forceinline__ uint32_t movm(uint32_t a) { uint32_t d; asm volatile("movmatrix.sync.aligned.m8n8.trans.b16 %0, %1;" : "=r"(d) : "r"(a)); return d; }
__device__ __forceinline__ float ex2(float x) { float y; asm("ex2.approx.ftz.f32 %0, %1;" : "=f"(y) : "f"(x)); return y; }
__device__ __forceinline__ float rcp(float x) { float y; asm("rcp.approx.ftz.f32 %0, %1;" : "=f"(y) : "f"(x)); return y; }
__device__ __forceinline__ uint32_t mapa(uint32_t a, uint32_t r) { uint32_t o; asm volatile("mapa.shared::cluster.u32 %0, %1, %2;" : "=r"(o) : "r"(a), "r"(r)); return o; }
__device__ __forceinline__ uint4 ld_poll16(const void* p) { uint4 v; asm volatile("ld.relaxed.gpu.global.v4.u32 {%0,%1,%2,%3}, [%4];" : "=r"(v.x), "=r"(v.y), "=r"(v.z), "=r"(v.w) : "l"(p) : "memory"); return v; }
__device__ __forceinline__ void st_rel16(void* p, uint4 v) { asm volatile("st.relaxed.gpu.global.v4.u32 [%0], {%1,%2,%3,%4};" ::"l"(p), "r"(v.x), "r"(v.y), "r"(v.z), "r"(v.w) : "memory"); }
__device__ __forceinline__ void st_rel4(void* p, uint32_t v) { asm volatile("st.relaxed.gpu.global.u32 [%0], %1;" ::"l"(p), "r"(v) : "memory"); }
__device__ __forceinline__ unsigned ld_acq(const unsigned* p) { unsigned v; asm volatile("ld.acquire.gpu.global.u32 %0, [%1];" : "=r"(v) : "l"(p) : "memory"); return v; }
__device__ __forceinline__ void red_rel(unsigned* p, unsigned v) { asm volatile("red.release.gpu.global.add.u32 [%0], %1;" ::"l"(p), "r"(v) : "memory"); }
__device__ __forceinline__ void bar_sync(int id, int n) { asm volatile("bar.sync %0, %1;" ::"r"(id), "r"(n) : "memory"); }
__device__ __forceinline__ void st_async8(uint32_t dst, uint32_t a, uint32_t b, uint32_t mb) {
    asm volatile("st.async.weak.shared::cluster.mbarrier::complete_tx::bytes.v2.b32 [%0], {%1,%2}, [%3];" ::"r"(dst), "r"(a), "r"(b), "r"(mb) : "memory");
}
__device__ __forceinline__ void st_async16(uint32_t dst, uint32_t a, uint32_t b, uint32_t c, uint32_t d, uint32_t mb) {
    asm volatile("st.async.weak.shared::cluster.mbarrier::complete_tx::bytes.v4.b32 [%0], {%1,%2,%3,%4}, [%5];" ::"r"(dst), "r"(a), "r"(b), "r"(c), "r"(d), "r"(mb) : "memory");
}
__device__ __forceinline__ uint2 lds64(uint32_t a) { uint2 v; asm volatile("ld.shared.v2.u32 {%0,%1}, [%2];" : "=r"(v.x), "=r"(v.y) : "r"(a) : "memory"); return v; }
__device__ __forceinline__ uint2 ld_poll8(const void* p) { uint2 v; asm volatile("ld.relaxed.gpu.global.v2.u32 {%0,%1}, [%2];" : "=r"(v.x), "=r"(v.y) : "l"(p) : "memory"); return v; }
__device__ __forceinline__ void bulk_s2s(uint32_t dst, uint32_t src, uint32_t bytes, uint32_t mb) {
    asm volatile("cp.async.bulk.shared::cluster.shared::cta.mbarrier::complete_tx::bytes [%0], [%1], %2, [%3];" ::"r"(dst), "r"(src), "r"(bytes), "r"(mb) : "memory");
}
__device__ __forceinline__ void bulk_g2s(uint32_t dst, const void* src, uint32_t bytes, uint32_t mb) {
    asm volatile("cp.async.bulk.shared::cluster.global.mbarrier::complete_tx::bytes [%0], [%1], %2, [%3];" ::"r"(dst), "l"(src), "r"(bytes), "r"(mb) : "memory");
}
__device__ __forceinline__ void tma3d(uint32_t dst, const CUtensorMap* tm, int c0, int c1, int c2, uint32_t mb) {
    asm volatile("cp.async.bulk.tensor.3d.shared::cluster.global.mbarrier::complete_tx::bytes [%0], [%1, {%3, %4, %5}], [%2];"
                 ::"r"(dst), "l"((uint64_t)tm), "r"(mb), "r"(c0), "r"(c1), "r"(c2) : "memory");
}
__device__ __forceinline__ void tma3d_mc(uint32_t dst, const CUtensorMap* tm, int c0, int c1, int c2, uint32_t mb, uint16_t mask) {
    asm volatile("cp.async.bulk.tensor.3d.shared::cluster.global.mbarrier::complete_tx::bytes.multicast::cluster [%0], [%1, {%3, %4, %5}], [%2], %6;"
                 ::"r"(dst), "l"((uint64_t)tm), "r"(mb), "r"(c0), "r"(c1), "r"(c2), "h"(mask) : "memory");
}
__device__ __forceinline__ void st_rel8(void* p, uint32_t a, uint32_t b) { asm volatile("st.relaxed.gpu.global.v2.u32 [%0], {%1,%2};" ::"l"(p), "r"(a), "r"(b) : "memory"); }
__device__ __forceinline__ void fence_async_smem() { asm volatile("fence.proxy.async.shared::cta;" ::: "memory"); }
__device__ __forceinline__ void fence_async_all() { asm volatile("fence.proxy.async;" ::: "memory"); }
__device__ __forceinline__ void cp_async16(uint32_t dst, const void* src) { asm volatile("cp.async.cg.shared.global [%0], [%1], 16;" ::"r"(dst), "l"(src) : "memory"); }
__device__ __forceinline__ void cluster_sync() { asm volatile("barrier.cluster.arrive.aligned; barrier.cluster.wait.aligned;" ::: "memory"); }
__device__ __forceinline__ int clk() { int c; asm volatile("mov.u32 %0, %%clock;" : "=r"(c)); return c; }

__device__ __forceinline__ void ldsm4(uint32_t* r, uint32_t a) { asm volatile("ldmatrix.sync.aligned.m8n8.x4.shared.b16 {%0,%1,%2,%3}, [%4];" : "=r"(r[0]), "=r"(r[1]), "=r"(r[2]), "=r"(r[3]) : "r"(a) : "memory"); }
__device__ __forceinline__ void ldsm2(uint32_t* r, uint32_t a) { asm volatile("ldmatrix.sync.aligned.m8n8.x2.shared.b16 {%0,%1}, [%2];" : "=r"(r[0]), "=r"(r[1]) : "r"(a) : "memory"); }
__device__ __forceinline__ void ldsm4t(uint32_t* r, uint32_t a) { asm volatile("ldmatrix.sync.aligned.m8n8.x4.trans.shared.b16 {%0,%1,%2,%3}, [%4];" : "=r"(r[0]), "=r"(r[1]), "=r"(r[2]), "=r"(r[3]) : "r"(a) : "memory"); }
__device__ __forceinline__ void ldsm2t(uint32_t* r, uint32_t a) { asm volatile("ldmatrix.sync.aligned.m8n8.x2.trans.shared.b16 {%0,%1}, [%2];" : "=r"(r[0]), "=r"(r[1]) : "r"(a) : "memory"); }
__device__ __forceinline__ void stsm4t(uint32_t a, uint32_t r0, uint32_t r1, uint32_t r2, uint32_t r3) {
    asm volatile("stmatrix.sync.aligned.m8n8.x4.trans.shared.b16 [%0], {%1,%2,%3,%4};" ::"r"(a), "r"(r0), "r"(r1), "r"(r2), "r"(r3) : "memory");
}
__device__ __forceinline__ uint4 lds128(uint32_t a) { uint4 v; asm volatile("ld.shared.v4.u32 {%0,%1,%2,%3}, [%4];" : "=r"(v.x), "=r"(v.y), "=r"(v.z), "=r"(v.w) : "r"(a) : "memory"); return v; }
__device__ __forceinline__ float2 lds64f(uint32_t a) { float2 v; asm volatile("ld.shared.v2.f32 {%0,%1}, [%2];" : "=f"(v.x), "=f"(v.y) : "r"(a) : "memory"); return v; }
__device__ __forceinline__ float lds32f(uint32_t a) { float v; asm volatile("ld.shared.f32 %0, [%1];" : "=f"(v) : "r"(a) : "memory"); return v; }
__device__ __forceinline__ uint32_t lds32(uint32_t a) { uint32_t v; asm volatile("ld.shared.u32 %0, [%1];" : "=r"(v) : "r"(a) : "memory"); return v; }
__device__ __forceinline__ void sts128(uint32_t a, uint4 v) { asm volatile("st.shared.v4.u32 [%0], {%1,%2,%3,%4};" ::"r"(a), "r"(v.x), "r"(v.y), "r"(v.z), "r"(v.w) : "memory"); }
__device__ __forceinline__ void sts128f(uint32_t a, float x, float y, float z, float w) { asm volatile("st.shared.v4.f32 [%0], {%1,%2,%3,%4};" ::"r"(a), "f"(x), "f"(y), "f"(z), "f"(w) : "memory"); }
__device__ __forceinline__ void sts64f(uint32_t a, float x, float y) { asm volatile("st.shared.v2.f32 [%0], {%1,%2};" ::"r"(a), "f"(x), "f"(y) : "memory"); }
__device__ __forceinline__ void sts64(uint32_t a, uint32_t x, uint32_t y) { asm volatile("st.shared.v2.u32 [%0], {%1,%2};" ::"r"(a), "r"(x), "r"(y) : "memory"); }
__device__ __forceinline__ void sts32f(uint32_t a, float x) { asm volatile("st.shared.f32 [%0], %1;" ::"r"(a), "f"(x) : "memory"); }

__device__ __forceinline__ void mma16(float* d, const uint32_t* a, uint32_t b0, uint32_t b1) {
    asm volatile("mma.sync.aligned.m16n8k16.row.col.f32.bf16.bf16.f32 {%0,%1,%2,%3}, {%4,%5,%6,%7}, {%8,%9}, {%0,%1,%2,%3};"
                 : "+f"(d[0]), "+f"(d[1]), "+f"(d[2]), "+f"(d[3]) : "r"(a[0]), "r"(a[1]), "r"(a[2]), "r"(a[3]), "r"(b0), "r"(b1));
}
__device__ __forceinline__ void mma16r(float* d, uint32_t a0, uint32_t a1, uint32_t a2, uint32_t a3, uint32_t b0, uint32_t b1) {
    asm volatile("mma.sync.aligned.m16n8k16.row.col.f32.bf16.bf16.f32 {%0,%1,%2,%3}, {%4,%5,%6,%7}, {%8,%9}, {%0,%1,%2,%3};"
                 : "+f"(d[0]), "+f"(d[1]), "+f"(d[2]), "+f"(d[3]) : "r"(a0), "r"(a1), "r"(a2), "r"(a3), "r"(b0), "r"(b1));
}
__device__ __forceinline__ void mma8(float* d, uint32_t a0, uint32_t a1, uint32_t b0) {
    asm volatile("mma.sync.aligned.m16n8k8.row.col.f32.bf16.bf16.f32 {%0,%1,%2,%3}, {%4,%5}, {%6}, {%0,%1,%2,%3};"
                 : "+f"(d[0]), "+f"(d[1]), "+f"(d[2]), "+f"(d[3]) : "r"(a0), "r"(a1), "r"(b0));
}
__device__ __forceinline__ void wgmma_n32(float* d, const uint32_t* a, uint32_t desc_lo, int sc) {
    asm volatile("{ .reg .pred p; .reg .b64 dd; setp.ne.b32 p, %21, 0; mov.b64 dd, {%20, 0x40000040};\n"
                 "wgmma.mma_async.sync.aligned.m64n32k16.f32.bf16.bf16 {%0,%1,%2,%3,%4,%5,%6,%7,%8,%9,%10,%11,%12,%13,%14,%15}, {%16,%17,%18,%19}, dd, p, 1, 1, 0; }\n"
                 : "+f"(d[0]), "+f"(d[1]), "+f"(d[2]), "+f"(d[3]), "+f"(d[4]), "+f"(d[5]), "+f"(d[6]), "+f"(d[7]),
                   "+f"(d[8]), "+f"(d[9]), "+f"(d[10]), "+f"(d[11]), "+f"(d[12]), "+f"(d[13]), "+f"(d[14]), "+f"(d[15])
                 : "r"(a[0]), "r"(a[1]), "r"(a[2]), "r"(a[3]), "r"(desc_lo), "r"(sc));
}
#define WG_FENCE() asm volatile("wgmma.fence.sync.aligned;" ::: "memory")
#define WG_COMMIT() asm volatile("wgmma.commit_group.sync.aligned;" ::: "memory")
#define WG_WAIT0() asm volatile("wgmma.wait_group.sync.aligned 0;" ::: "memory")
__device__ __forceinline__ uint32_t desc_sw128(uint32_t saddr) { return ((saddr & 0x3FFFF) >> 4) | (1u << 16); }
__device__ __forceinline__ uint32_t pack2(float lo, float hi) { __nv_bfloat162 h = __floats2bfloat162_rn(lo, hi); return *(uint32_t*)&h; }
__device__ __forceinline__ float bflo(uint32_t u) { return __uint_as_float(u << 16); }
__device__ __forceinline__ float bfhi(uint32_t u) { return __uint_as_float(u & 0xffff0000u); }
__device__ __forceinline__ float rbf(float x) { return __uint_as_float(pack2(0.f, x)); }
__device__ __forceinline__ uint32_t nzw(uint32_t u) { return u == 0 ? 0x80008000u : u; }
__device__ __forceinline__ uint32_t min4(uint4 v) { return min(min(v.x, v.y), min(v.z, v.w)); }
__device__ __forceinline__ void mbar_arrive_if(uint32_t mb, uint32_t c) {
    asm volatile("{ .reg .pred p; setp.ne.u32 p, %1, 0; @p mbarrier.arrive.shared.b64 _, [%0]; }" ::"r"(mb), "r"(c) : "memory");
}
__device__ __forceinline__ int eperm(int p) { return (p & ~15) + 2 * (p & 7) + ((p >> 3) & 1); }

constexpr int U_STRIDE = 136 * 48;
constexpr int KR_STRIDE = 2080 * 2 * 2;
constexpr int B_U_OFF = 0, B_KR_OFF = 8 * U_STRIDE, B_CONV_END = B_KR_OFF + 8 * KR_STRIDE;
constexpr int B_OX_STAGES = 3, B_OX_BYTES = 40960;
constexpr int B_BAR_OFF = B_OX_STAGES * B_OX_BYTES;
constexpr int B_SMEM = B_BAR_OFF + 128;

constexpr int B_THREADS = 384;
constexpr int B_LAG = 2;

struct AuxArgs { const bf16 *x, *Wo, *Bk, *Bv, *shk, *ssmk, *ssmD, *gatew; bf16* out; };
constexpr int MBB_FULL = B_BAR_OFF, MBB_EMPTY = B_BAR_OFF + 24, MBB_ST = B_BAR_OFF + 48, MBB_GO = B_BAR_OFF + 80, MBB_FLAG = B_BAR_OFF + 96;

__device__ __forceinline__ void aux_init(uint32_t sb) {
    for (int i = 0; i < B_OX_STAGES; i++) { mbar_init(sb + MBB_FULL + 8 * i, 1); mbar_init(sb + MBB_EMPTY + 8 * i, 8); }
    for (int i = 0; i < 4; i++) mbar_init(sb + MBB_ST + 8 * i, 8);
    mbar_init(sb + MBB_GO, 8);
    fence_async_smem();
}
__device__ __forceinline__ bool mbar_test(uint32_t mb, int parity) {
    uint32_t ok;
    asm volatile("{ .reg .pred p; mbarrier.test_wait.parity.shared.b64 p, [%1], %2; selp.u32 %0, 1, 0, p; }" : "=r"(ok) : "r"(mb), "r"(parity) : "memory");
    return ok;
}
__device__ __forceinline__ void aux_control(uint32_t sb, int cta) {
    const int kg = cta / NCR_, cr = cta % NCR_;
    const int h0 = kg < 4 ? kg * 5 : 20 + (kg - 4) * 4, nh = kg < 4 ? 5 : 4;
    { int guard = 0; while (!mbar_try(sb + MBB_GO, 0)) { if (++guard > (1 << 22)) break; } }
    red_rel(&g_misc[0], 1);
    int nl = 0, nr = 0, guard = 0;
    while (nr < NSEG_) {
        bool did = false;
        if (nl < NSEG_) {
            const int st = nl % B_OX_STAGES;
            if ((nl < B_OX_STAGES || mbar_test(sb + MBB_EMPTY + 8 * st, (nl / B_OX_STAGES - 1) & 1)) &&
                ld_acq(&g_oxcnt[nl * 8 + kg]) >= (unsigned)(2 * nh)) {
                fence_async_all();
                mbar_expect(sb + MBB_FULL + 8 * st, nh * 8192);
                bulk_g2s(sb + st * B_OX_BYTES, g_ox + (size_t)(nl * NH_ + h0) * 512, nh * 8192, sb + MBB_FULL + 8 * st);
                nl++; did = true;
            }
        }
        if (nr < nl && mbar_test(sb + MBB_ST + 8 * (nr & 3), (nr >> 2) & 1)) { red_rel(&g_pcnt[nr * 8 + cr], 1); nr++; did = true; }
        if (did) guard = 0;
        else { if (++guard > (1 << 17)) { g_misc[2] = 4; break; } __nanosleep(100); }
    }
}
__device__ __forceinline__ void aux_compute(const AuxArgs& P, unsigned char* smem, uint32_t sb, int cta, int warp) {
    const bf16* __restrict__ x = P.x; const bf16* __restrict__ Wo = P.Wo; const bf16* __restrict__ Bk = P.Bk; const bf16* __restrict__ Bv = P.Bv;
    const bf16* __restrict__ shk = P.shk; const bf16* __restrict__ ssmk = P.ssmk; const bf16* __restrict__ ssmD = P.ssmD;
    const bf16* __restrict__ gatew = P.gatew; bf16* __restrict__ out = P.out;
    const int tid = threadIdx.x, lane = tid & 31;
    const int g = lane >> 2, t = lane & 3;
    const int kg = cta / NCR_, cr = cta % NCR_;
    const int h0 = kg < 4 ? kg * 5 : 20 + (kg - 4) * 4, nh = kg < 4 ? 5 : 4;
    const uint32_t mb_full = sb + MBB_FULL, mb_empty = sb + MBB_EMPTY, mb_st = sb + MBB_ST, mb_go = sb + MBB_GO;
    CAL(112 + cta, 0);
    {
        uint32_t wv[10];
#pragma unroll
        for (int i = 0; i < 10; i++) wv[i] = __ldg((const uint32_t*)gatew + lane + 32 * i);
        uint32_t xv[8][10];
#pragma unroll
        for (int j = 0; j < 8; j++) {
            const int r = min(cta * 8 + warp + j * (NB_CTAS * 8), S_ - 1);
#pragma unroll
            for (int i = 0; i < 10; i++) xv[j][i] = __ldg((const uint32_t*)(x + (size_t)r * DM_) + lane + 32 * i);
        }
#pragma unroll
        for (int j = 0; j < 8; j++) {
            const int r = cta * 8 + warp + j * (NB_CTAS * 8);
            float acc = 0.f;
#pragma unroll
            for (int i = 0; i < 10; i++) acc += rbf(bflo(xv[j][i]) * bflo(wv[i])) + rbf(bfhi(xv[j][i]) * bfhi(wv[i]));
#pragma unroll
            for (int o = 16; o; o >>= 1) acc += __shfl_xor_sync(~0u, acc, o);
            if (lane == 0 && r < S_) g_gate[r] = rbf(1.f / (1.f + __expf(-rbf(acc))));
        }
    }

    for (int item = (cta + 19) % NB_CTAS; item < 80; item += NB_CTAS) {
        const int c0 = item * 8;
        bar_sync(1, 256);
        for (int i = tid; i < 8 * 24; i += 256) sts128(sb + B_U_OFF + (i / 24) * U_STRIDE + (i % 24) * 16, make_uint4(0, 0, 0, 0));
        {
            const uint32_t krb = sb + B_KR_OFF + warp * KR_STRIDE;
            const bf16* kp = ssmk + (size_t)(c0 + warp) * S_;
            uint4 v[8]; uint32_t pv[8];
#pragma unroll
            for (int j = 0; j < 8; j++) {
                const int i = lane + 32 * j;
                v[j] = __ldg((const uint4*)kp + i);
                pv[j] = i > 0 ? __ldg((const uint32_t*)kp + 4 * i - 1) : 0u;
            }
#pragma unroll
            for (int j = 0; j < 8; j++) {
                const int i = lane + 32 * j;
                sts128(krb + (2040 - 8 * i) * 2, make_uint4(__byte_perm(v[j].w, 0, 0x1032), __byte_perm(v[j].z, 0, 0x1032),
                                                            __byte_perm(v[j].y, 0, 0x1032), __byte_perm(v[j].x, 0, 0x1032)));
                sts128(krb + 4160 + (2040 - 8 * i) * 2, make_uint4(__byte_perm(v[j].w, v[j].z, 0x7610), __byte_perm(v[j].z, v[j].y, 0x7610),
                                                                   __byte_perm(v[j].y, v[j].x, 0x7610), __byte_perm(v[j].x, pv[j], 0x7610)));
            }
            if (lane < 4) { sts128(krb + 4096 + lane * 16, make_uint4(0, 0, 0, 0)); sts128(krb + 4160 + 4096 + lane * 16, make_uint4(0, 0, 0, 0)); }
        }
        {
            float sh[8][4];
#pragma unroll
            for (int c = 0; c < 8; c++) {
                uint2 v = __ldg((const uint2*)(shk + (c0 + c) * 4));
                sh[c][0] = bflo(v.x); sh[c][1] = bfhi(v.x); sh[c][2] = bflo(v.y); sh[c][3] = bfhi(v.y);
            }
            const int t0 = tid * 8;
            uint4 kr[11], vr[8];
#pragma unroll
            for (int i = 0; i < 11; i++) { int r = t0 - 3 + i; kr[i] = r >= 0 ? __ldg((const uint4*)(Bk + (size_t)r * DM_ + c0)) : make_uint4(0, 0, 0, 0); }
#pragma unroll
            for (int i = 0; i < 8; i++) vr[i] = __ldg((const uint4*)(Bv + (size_t)(t0 + i) * DM_ + c0));
#pragma unroll
            for (int c = 0; c < 8; c++) {
                float res[8];
#pragma unroll
                for (int i = 0; i < 8; i++) {
                    float a = 0.f;
#pragma unroll
                    for (int tt = 0; tt < 4; tt++) {
                        uint32_t wd = ((const uint32_t*)&kr[i + tt])[c >> 1];
                        float kv_ = (c & 1) ? bfhi(wd) : bflo(wd);
                        a = rbf(a + rbf(kv_ * sh[c][3 - tt]));
                    }
                    uint32_t wd = ((const uint32_t*)&vr[i])[c >> 1];
                    res[i] = a * ((c & 1) ? bfhi(wd) : bflo(wd));
                }
                uint4 o = make_uint4(pack2(res[0], res[1]), pack2(res[2], res[3]), pack2(res[4], res[5]), pack2(res[6], res[7]));
                sts128(sb + B_U_OFF + c * U_STRIDE + (8 + (tid >> 1)) * 48 + (tid & 1) * 16, o);
            }
        }
        bar_sync(1, 256);
        {
            float acc[16][4];
#pragma unroll
            for (int i = 0; i < 64; i++) ((float*)acc)[i] = 0.f;
            const uint32_t kb = sb + B_KR_OFF + warp * KR_STRIDE + ((g & 1) ? (2047 - g + 2 * t) * 2 : 4160 + (2046 - g + 2 * t) * 2);
            const uint32_t ub = sb + B_U_OFF + warp * U_STRIDE + (8 + (lane & 7) + (lane >> 4) * 8) * 48 + ((lane >> 3) & 1) * 16;
#pragma unroll 1
            for (int r = 0; r < 8; r++) {
                uint32_t pa[16][3];
#pragma unroll
                for (int m = 0; m < 16; m++) {
                    const uint32_t a = kb - (16 * (r + 8 * m)) * 2;
                    pa[m][0] = lds32(a + 16); pa[m][1] = lds32(a); pa[m][2] = lds32(a - 16);
                }
#pragma unroll
                for (int d = 0; d < 16; d += 2) {
                    uint32_t b[4];
                    ldsm4(b, ub + (8 * d - r) * 48);
#pragma unroll
                    for (int m = 0; m < 16 - d; m++) mma16r(acc[m + d], pa[m][1], pa[m][2], pa[m][0], pa[m][1], b[0], b[1]);
#pragma unroll
                    for (int m = 0; m < 15 - d; m++) mma16r(acc[m + d + 1], pa[m][1], pa[m][2], pa[m][0], pa[m][1], b[2], b[3]);
                }
            }
            __syncwarp();
            const float Dv = __bfloat162float(ssmD[c0 + warp]);
            bf16* u = (bf16*)(smem + B_U_OFF + warp * U_STRIDE) + 8 * 24;
#pragma unroll
            for (int i = 0; i < 16; i++) {
#pragma unroll
                for (int q = 0; q < 4; q++) {
                    const int idx = (8 * i + 2 * t + (q & 1)) * 24 + g + (q >> 1) * 8;
                    const float kvv = __bfloat162float(u[idx]);
                    u[idx] = __float2bfloat16_rn(rbf(acc[i][q]) + rbf(kvv * Dv));
                }
            }
        }
        uint4 xv[8];
#pragma unroll
        for (int j = 0; j < 8; j++) xv[j] = __ldg((const uint4*)(x + (size_t)(tid + 256 * j) * DM_ + c0));
        bar_sync(1, 256);
#pragma unroll
        for (int j = 0; j < 8; j++) {
            const int r = tid + 256 * j;
            uint32_t o[4];
            const bf16* u = (const bf16*)(smem + B_U_OFF) + (8 + (r >> 4)) * 24 + (r & 15);
#pragma unroll
            for (int c = 0; c < 4; c++) {
                uint32_t wd = ((const uint32_t*)&xv[j])[c];
                o[c] = pack2(bflo(wd) * __bfloat162float(u[(2 * c) * (U_STRIDE / 2)]), bfhi(wd) * __bfloat162float(u[(2 * c + 1) * (U_STRIDE / 2)]));
            }
            *(uint4*)(g_b + (size_t)r * DM_ + c0) = make_uint4(o[0], o[1], o[2], o[3]);
        }
    }
    fence_async_smem();
    __syncwarp();
    if (lane == 0) mbar_arrive(mb_go);
    CAL(112 + cta, 1);

    const int wg = warp >> 2, w = warp & 3;
    const int col = cr * 128 + wg * 64 + 16 * w + 2 * g;
    uint32_t A[40][4];
#pragma unroll
    for (int ks = 0; ks < 40; ks++) {
        const int hh = ks >> 3;
        uint32_t r[4] = {0, 0, 0, 0};
        if (hh < nh) {
#pragma unroll
            for (int i = 0; i < 4; i++) {
                const int p = (ks & 7) * 16 + 2 * t + (i & 1) + (i >> 1) * 8;
                r[i] = __ldg((const uint32_t*)(Wo + (size_t)((h0 + hh) * 128 + eperm(p)) * DM_ + col));
            }
        }
        A[ks][0] = __byte_perm(r[0], r[1], 0x5410); A[ks][1] = __byte_perm(r[0], r[1], 0x7632);
        A[ks][2] = __byte_perm(r[2], r[3], 0x5410); A[ks][3] = __byte_perm(r[2], r[3], 0x7632);
    }
    CAL(112 + cta, 2);
    auto finalize = [&](int n) {
        const int r = kg + 7 * warp;
        if (r < 32) {
            if (lane == 0) {
                int guard = 0;
                while (ld_acq(&g_pcnt[n * 8 + cr]) < (unsigned)NKG_) { if (++guard > (1 << 18)) { g_misc[2] = 6; break; } __nanosleep(50); }
                if (n == 0) { guard = 0; while (ld_acq(&g_misc[0]) < (unsigned)NB_CTAS) { if (++guard > (1 << 22)) break; __nanosleep(200); } }
            }
            __syncwarp();
            const int row = n * 32 + r, c = cr * 128 + lane * 4;
            float4 v[NKG_];
#pragma unroll
            for (int k = 0; k < NKG_; k++) v[k] = __ldcg((const float4*)(g_part + ((size_t)k * S_ + row) * DM_ + c));
            const float gt = __ldcg(&g_gate[row]), og = rbf(1.f - gt);
            const uint2 bv = __ldcg((const uint2*)(g_b + (size_t)row * DM_ + c));
            float4 a = v[0];
#pragma unroll
            for (int k = 1; k < NKG_; k++) { a.x += v[k].x; a.y += v[k].y; a.z += v[k].z; a.w += v[k].w; }
            uint2 o;
            o.x = pack2(rbf(gt * rbf(a.x)) + rbf(og * bflo(bv.x)), rbf(gt * rbf(a.y)) + rbf(og * bfhi(bv.x)));
            o.y = pack2(rbf(gt * rbf(a.z)) + rbf(og * bflo(bv.y)), rbf(gt * rbf(a.w)) + rbf(og * bfhi(bv.y)));
            *(uint2*)(out + (size_t)row * DM_ + c) = o;
        }
    };
#pragma unroll 1
    for (int n = 0; n < NSEG_; n++) {
        const int st = n % B_OX_STAGES;
        { int guard = 0; while (!mbar_try(mb_full + 8 * st, (n / B_OX_STAGES) & 1)) { if (++guard > (1 << 20)) break; } }
        __syncwarp();
        float acc[16];
        const uint32_t d0 = __shfl_sync(0xffffffffu, desc_sw128(sb + st * B_OX_BYTES), 0);
        WG_FENCE();
#pragma unroll
        for (int ks = 0; ks < 32; ks++) wgmma_n32(acc, A[ks], d0 + (((ks >> 2) * 4096 + (ks & 3) * 32) >> 4), ks > 0);
        if (nh == 5) {
#pragma unroll
            for (int ks = 32; ks < 40; ks++) wgmma_n32(acc, A[ks], d0 + (((ks >> 2) * 4096 + (ks & 3) * 32) >> 4), 1);
        }
        WG_COMMIT();
        WG_WAIT0();
        if (lane == 0) mbar_arrive(mb_empty + 8 * st);
        float* pp = g_part + ((size_t)kg * S_ + n * 32) * DM_ + col;
#pragma unroll
        for (int j = 0; j < 4; j++) {
            *(float2*)(pp + (size_t)(8 * j + 2 * t) * DM_) = make_float2(acc[4 * j], acc[4 * j + 2]);
            *(float2*)(pp + (size_t)(8 * j + 2 * t + 1) * DM_) = make_float2(acc[4 * j + 1], acc[4 * j + 3]);
        }
        __syncwarp();
        if (lane == 0) mbar_arrive(mb_st + 8 * (n & 3));
        if (n >= B_LAG) finalize(n - B_LAG);
    }
    for (int n = NSEG_ - B_LAG; n < NSEG_; n++) finalize(n);
    CAL(112 + cta, 3);
    bar_sync(1, 256);
    volatile unsigned* flag = (volatile unsigned*)(smem + MBB_FLAG);
    if (tid == 0) {
        unsigned old; asm volatile("atom.acq_rel.gpu.global.add.u32 %0, [%1], 1;" : "=r"(old) : "l"(&g_misc[1]) : "memory");
        *flag = (old == NB_CTAS - 1);
    }
    bar_sync(1, 256);
    if (*flag) {
        for (int i = tid; i < NSEG_ * 8; i += 256) { g_oxcnt[i] = 0; g_pcnt[i] = 0; }
        if (tid == 0) { g_misc[0] = 0; g_misc[1] = 0; }
    }
}

constexpr int N_SPARE = 16;
__global__ void __launch_bounds__(B_THREADS, 1) aux_kernel(const AuxArgs P) {
    extern __shared__ __align__(1024) unsigned char smem[];
    const uint32_t sb = __shfl_sync(0xffffffffu, smem_u32(smem), 0);
    const int warp = __shfl_sync(0xffffffffu, threadIdx.x >> 5, 0);
    const int cta = N_SPARE + blockIdx.x;
    if (threadIdx.x == 0) aux_init(sb);
    __syncthreads();
    if (warp >= 8) {
        asm volatile("setmaxnreg.dec.sync.aligned.u32 56;");
        if (threadIdx.x == 256) aux_control(sb, cta);
    } else {
        asm volatile("setmaxnreg.inc.sync.aligned.u32 224;");
        aux_compute(P, smem, sb, cta, warp);
    }
}

constexpr int XT_OFF = 0, WO_OFF = 81920, WO_STRIDE = 464, KV_STRIDE = 272, XB_BYTES = 32 * KV_STRIDE, QX_BYTES = 16 * KV_STRIDE,
              K_OFF = 141312, V_OFF = K_OFF + 2 * XB_BYTES, EX_OFF = V_OFF + 2 * XB_BYTES  ,
              QX_OFF = EX_OFF + XB_BYTES, QF_OFF = QX_OFF + 2 * QX_BYTES, KF_OFF = QF_OFF + 2048, VF_OFF = KF_OFF + 4096,
              IN_OFF = VF_OFF + 4096, M_OFF = IN_OFF + 7680, EX2_OFF = M_OFF + 10240 + 512  ,
              BAR_OFF = EX2_OFF + XB_BYTES, A_SMEM = BAR_OFF + 128;
constexpr int O_OFF = QF_OFF;
__device__ __forceinline__ uint32_t kv_off(int which, int role, int n) {
    const int base = which == 1 ? K_OFF : V_OFF;
    if (which != role) return base + (n & 1) * XB_BYTES;
    const int j = n % 3;
    return j == 2 ? EX_OFF : base + j * XB_BYTES;
}
__device__ __forceinline__ void tile_owner(int T, int nown, int& gr, int& rk, int& sl) {
    gr = T >= 28 ? 2 : (T >= 14 ? 1 : 0);
    int i = T - 14 * gr;
    sl = i >= nown; i -= sl * nown;
    const int r = i + 5 * gr;
    rk = r >= nown ? r - nown : r;
}
constexpr int MB_X = BAR_OFF  , MB_M = BAR_OFF + 16  , MB_IN = BAR_OFF + 40  , MB_QC = BAR_OFF + 120, MB_H1 = BAR_OFF + 64,
              MB_KV = BAR_OFF + 72  , MB_FREE = BAR_OFF + 88  , MB_XD = BAR_OFF + 104  ;
constexpr float SCALE = 0.08838834764831845f;
constexpr float LOG2E = 1.4426950408889634f;
constexpr int A_THREADS = 384, A_CTAS = 112;

#define FRESH_LANE() int lane = lane_r; asm volatile("" : "+r"(lane)); const int g = lane >> 2, t = lane & 3; const uint32_t l16 = lane * 16; (void)g; (void)t; (void)l16
#define PIN(x) asm volatile("" ::"r"(x))
#define TS(i) do {} while (0)
#define TSV(i, cond, val) do {} while (0)

__global__ void __launch_bounds__(A_THREADS, 1)
rec_kernel(const __grid_constant__ CUtensorMap tmx, const bf16* __restrict__ mem0, const bf16* __restrict__ Wq,
           const bf16* __restrict__ Wk, const bf16* __restrict__ Wv, const bf16* __restrict__ Wo, const AuxArgs P) {
    extern __shared__ __align__(1024) unsigned char smem[];
    const uint32_t sb = __shfl_sync(0xffffffffu, smem_u32(smem), 0);
    const int tid = threadIdx.x, warp = __shfl_sync(0xffffffffu, tid >> 5, 0);
    const int lane = tid & 31;
    const int g = lane >> 2, t = lane & 3;
    uint32_t rank; asm volatile("mov.u32 %0, %%cluster_ctarank;" : "=r"(rank));
    const int cl = blockIdx.x >> 4;
    const int nh = cl < 4 ? 5 : 4;
    const int hl = rank / 3, role = rank - 3 * hl, tb = 3 * hl;
    const int head = (cl < 4 ? 5 * cl : 20 + 4 * (cl - 4)) + hl;
    const bool is_head = hl < nh;
    const int nown = 3 * nh;

    const int worker = cl < 4 ? cl : 4 + (cl - 4) * 4 + ((int)rank - 12);
    asm volatile("griddepcontrol.launch_dependents;");
    CAL(blockIdx.x, 0);
    if (tid == 0) {
        mbar_init(sb + MB_X, 1); mbar_init(sb + MB_X + 8, 1);
        for (int j = 0; j < 3; j++) mbar_init(sb + MB_M + 8 * j, 1);
        mbar_init(sb + MB_IN, 1); mbar_init(sb + MB_IN + 8, 1); mbar_init(sb + MB_IN + 16, 1); mbar_init(sb + MB_QC, 3);
        mbar_init(sb + MB_H1, 1); mbar_init(sb + MB_KV, 1); mbar_init(sb + MB_KV + 8, 1);
        mbar_init(sb + MB_FREE, 2); mbar_init(sb + MB_FREE + 8, 2); mbar_init(sb + MB_XD, 8); mbar_init(sb + MB_XD + 8, 8);
        asm volatile("fence.mbarrier_init.release.cluster;" ::: "memory");
        fence_async_smem();
        mbar_expect(sb + MB_X, 40960); mbar_expect(sb + MB_X + 8, 40960);
        if (!is_head) aux_init(sb);
    }
    __syncthreads();
    cluster_sync();
    const uint16_t tmask = (uint16_t)(7u << tb);
    if (tid == 0 && is_head) {
        for (int n = 0; n < 2; n++)
            for (int kb = role; kb < 10; kb += 3) tma3d_mc(sb + XT_OFF + n * 40960 + kb * 4096, &tmx, 0, 32 * n, kb, sb + MB_X + 8 * n, tmask);
    }

    if (warp < 8) {
        asm volatile("setmaxnreg.inc.sync.aligned.u32 224;");
        if (is_head) {
        const int lane_r = __shfl_sync(0xffffffffu, tid & 31, tid & 31);
        const int wg = warp >> 2, w = warp & 3;
        uint32_t A[40][4];
        {
            const bf16* W = role == 0 ? Wq : (role == 1 ? Wk : Wv);
            const bf16* wp = W + (size_t)(2 * t) * 4096 + head * 128 + 16 * warp + 2 * g;
#pragma unroll
            for (int ks = 0; ks < 40; ks++) {
                A[ks][0] = __ldg((const uint32_t*)(wp + (size_t)(16 * ks) * 4096));
                A[ks][1] = __ldg((const uint32_t*)(wp + (size_t)(16 * ks + 1) * 4096));
                A[ks][2] = __ldg((const uint32_t*)(wp + (size_t)(16 * ks + 8) * 4096));
                A[ks][3] = __ldg((const uint32_t*)(wp + (size_t)(16 * ks + 9) * 4096));
            }
#pragma unroll
            for (int ks = 0; ks < 40; ks++) {
                const uint32_t r0 = A[ks][0], r1 = A[ks][1], r2 = A[ks][2], r3 = A[ks][3];
                A[ks][0] = __byte_perm(r0, r1, 0x5410); A[ks][1] = __byte_perm(r0, r1, 0x7632);
                A[ks][2] = __byte_perm(r2, r3, 0x5410); A[ks][3] = __byte_perm(r2, r3, 0x7632);
            }
        }

        auto xproj = [&](int n) {
            const int st = n & 1;
            FRESH_LANE();
            const uint32_t a = sb + (role == 0 ? (st ? EX2_OFF : EX_OFF) : kv_off(role, role, n)) + (8 * (lane >> 4) + (lane & 7)) * KV_STRIDE + 32 * warp + ((lane >> 3) & 1) * 16;
            PIN(a);
            if (role == 0) { if (n >= 2) mbar_wait_u(sb + MB_QC, st); }
            else if (n >= 3) mbar_wait_u(sb + MB_FREE + 8 * ((n - 3) & 1), ((n - 3) >> 1) & 1);
            mbar_wait_u(sb + MB_X + 8 * st, (n >> 1) & 1);
            float acc[16];
            const uint32_t d0 = __shfl_sync(0xffffffffu, desc_sw128(sb + XT_OFF + st * 40960), 0);
            WG_FENCE();
#pragma unroll
            for (int ks = 0; ks < 40; ks++) wgmma_n32(acc, A[ks], d0 + (((ks >> 2) * 4096 + (ks & 3) * 32) >> 4), ks > 0);
            WG_COMMIT();
            WG_WAIT0();
            stsm4t(a, pack2(acc[0], acc[1]), pack2(acc[2], acc[3]), pack2(acc[4], acc[5]), pack2(acc[6], acc[7]));
            stsm4t(a + 16 * KV_STRIDE, pack2(acc[8], acc[9]), pack2(acc[10], acc[11]), pack2(acc[12], acc[13]), pack2(acc[14], acc[15]));
            fence_async_smem();
            __syncwarp();
            if (lane == 0) mbar_arrive(sb + MB_XD + 8 * st);
        };

        xproj(0);
        xproj(1);
#pragma unroll 1
        for (int s = 0; s < NSEG_; s++) {
            const int st = s & 1;
            if (warp == 4 && lane_r == 0) mbar_expect(sb + MB_H1, 6144);
            {
                float acc[4][4];
#pragma unroll
                for (int i = 0; i < 16; i++) ((float*)acc)[i] = 0.f;
                FRESH_LANE();
                const uint32_t mrd = sb + M_OFF + lane * 8;
                const uint32_t dl = sb + (role == 0 ? QF_OFF : (role == 1 ? KF_OFF : VF_OFF) + st * 2048) + warp * 256 + lane * 8;
                PIN(mrd); PIN(dl);
                uint2 b[40];
                mbar_wait_u(sb + MB_M, st);
                TS(0);
#pragma unroll
                for (int i = 0; i < 12; i++) b[i] = lds64(mrd + i * 256);
#pragma unroll
                for (int i = 0; i < 40; i++) {
                    if (i == 2) mbar_wait_u(sb + MB_M + 8, st);
                    if (i == 16) mbar_wait_u(sb + MB_M + 16, st);
                    if (i + 12 < 40) b[i + 12] = lds64(mrd + (i + 12) * 256);
                    mma16(acc[i & 3], A[i], b[i].x, b[i].y);
                }
                TS(1);
                uint32_t u0 = pack2((acc[0][0] + acc[1][0]) + (acc[2][0] + acc[3][0]), (acc[0][1] + acc[1][1]) + (acc[2][1] + acc[3][1]));
                uint32_t u1 = pack2((acc[0][2] + acc[1][2]) + (acc[2][2] + acc[3][2]), (acc[0][3] + acc[1][3]) + (acc[2][3] + acc[3][3]));
                if (role != 2) { u0 = movm(u0); u1 = movm(u1); }
#pragma unroll
                for (int r = 0; r < 3; r++) st_async8(mapa(dl, tb + r), u0, u1, mapa(sb + MB_H1, tb + r));
            }
            TS(2);
            if (s == NSEG_ - 1) break;
            uint32_t wa[8][4];
            const bool pair = wg || (w >= 2 && role != 2);
            const int tileA = wg ? 2 * w : (pair ? 6 + 2 * w : 8 + w);
            const uint32_t stg_hi = pair ? 32u : 64u * WO_STRIDE;
            int wA, rA, sA, wB, rB, sB;
            tile_owner(role * 14 + tileA, nown, wA, rA, sA); tile_owner(role * 14 + tileA + 1, nown, wB, rB, sB);
            uint32_t wb, inA, inB;
            {
                FRESH_LANE();
                wb = sb + WO_OFF + ((lane & 7) + (lane >> 4) * 8 + 64) * WO_STRIDE + ((lane >> 3) & 1) * 16 + tileA * 32;
                inA = mapa(sb + IN_OFF + (wA * 2 + sA) * 1280 + hl * 256 + lane * 8, rA); inB = mapa(sb + IN_OFF + (wB * 2 + sB) * 1280 + hl * 256 + lane * 8, rB);
                PIN(wb); PIN(inA); PIN(inB);
            }
            if (wg) {
                FRESH_LANE();
#pragma unroll
                for (int ks = 0; ks < 8; ks++) ldsm4t(wa[ks], wb - 64 * WO_STRIDE + (ks & 3) * 16 * WO_STRIDE + (ks >> 2) * stg_hi);
                if (w < 2) {
                    mbar_wait_u(sb + MB_H1, st);
                    if (lane == 0) {
                        if (w == 0) { mbar_expect(sb + MB_M, 3584); mbar_expect(sb + MB_M + 8, 3584); mbar_expect(sb + MB_M + 16, 3072); }
                        else {
                            for (int n = (s == 0 ? 2 : s + 3); n <= s + 3 && n < NSEG_; n++) {
                                mbar_expect(sb + MB_X + 8 * (n & 1), 40960);
                                for (int kb = role; kb < 10; kb += 3)
                                    tma3d_mc(sb + XT_OFF + (n & 1) * 40960 + kb * 4096, &tmx, 0, 32 * n, kb, sb + MB_X + 8 * (n & 1), tmask);
                            }
                        }
                    }
                    __syncwarp();
                }
            } else {
                FRESH_LANE();
                const uint32_t s_base = sb + M_OFF + role * 3584;
                const uint32_t r8 = (lane & 7) * KV_STRIDE;
                const int mt = w & 1, eh = w >> 1;
                mbar_wait_u(sb + MB_KV + 8 * st, (s >> 1) & 1);
                if (w == 3 && lane == 0) asm volatile("mbarrier.arrive.relaxed.cluster.shared::cluster.b64 _, [%0];" ::"r"(mapa(sb + MB_QC, tb)) : "memory");
                uint32_t vb[2][2][4];
                uint2 vm[2];
                {
                    const uint32_t ka = sb + kv_off(1, role, s) + eh * 128 + r8 + (16 * mt + ((lane >> 3) & 1) * 8) * KV_STRIDE + (lane >> 4) * 16;
                    const uint32_t fl = sb + lane * 8;
                    const uint32_t sw = s_base + eh * 1280 + mt * 64 + t * 320 + g * 4;
                    const uint32_t sm = s_base + 2560 + w * 256 + t * 64 + g * 4;
                    uint32_t a[4][4];
#pragma unroll
                    for (int k = 0; k < 4; k++) ldsm4(a[k], ka + k * 32);
                    const uint32_t va1 = sb + kv_off(2, role, s) + w * 64 + r8 + ((lane >> 3) & 1) * 8 * KV_STRIDE + (lane >> 4) * 16;
                    ldsm4t(vb[0][0], va1); ldsm4t(vb[0][1], va1 + 32);
                    ldsm4t(vb[1][0], va1 + 16 * KV_STRIDE); ldsm4t(vb[1][1], va1 + 16 * KV_STRIDE + 32);
                    PIN(fl); PIN(sw); PIN(sm);
                    mbar_wait_u(sb + MB_H1, st);
                    TS(3);
                    uint2 b[4], am[2], bm[2];
#pragma unroll
                    for (int k = 0; k < 4; k++) b[k] = lds64(fl + QF_OFF + (4 * eh + k) * 256);
#pragma unroll
                    for (int k = 0; k < 2; k++) { am[k] = lds64(fl + KF_OFF + st * 2048 + (2 * w + k) * 256); bm[k] = lds64(fl + QF_OFF + (2 * w + k) * 256); }
                    float c0[4] = {0, 0, 0, 0}, c1[4] = {0, 0, 0, 0}, c2[4] = {0, 0, 0, 0}, c3[4] = {0, 0, 0, 0};
                    mma16(c0, a[0], b[0].x, b[0].y); mma16(c1, a[1], b[1].x, b[1].y);
                    mma16r(c2, am[0].x, 0u, am[0].y, 0u, bm[0].x, bm[0].y);
                    mma16r(c3, am[1].x, 0u, am[1].y, 0u, bm[1].x, bm[1].y);
                    mma16(c0, a[2], b[2].x, b[2].y); mma16(c1, a[3], b[3].x, b[3].y);
                    sts32f(sm, c2[0] + c3[0]); sts32f(sm + 32, c2[1] + c3[1]);
                    sts32f(sw, c0[0] + c1[0]); sts32f(sw + 160, c0[1] + c1[1]);
                    sts32f(sw + 32, c0[2] + c1[2]); sts32f(sw + 160 + 32, c0[3] + c1[3]);
#pragma unroll
                    for (int k = 0; k < 2; k++) vm[k] = lds64(fl + VF_OFF + st * 2048 + (2 * w + k) * 256);
                }
                const uint32_t sr = s_base + g * 160 + t * 8;
                bar_sync(7, 128);
                TS(4);
                float sc[10];
                {
                    float2 m[4], p0[4], p1[4];
#pragma unroll
                    for (int j = 0; j < 4; j++) { p0[j] = lds64f(sr + j * 32); p1[j] = lds64f(sr + 1280 + j * 32); }
#pragma unroll
                    for (int j = 0; j < 4; j++) m[j] = lds64f(s_base + 2560 + j * 256 + lane * 8);
#pragma unroll
                    for (int j = 0; j < 4; j++) { sc[2 + 2 * j] = p0[j].x + p1[j].x; sc[3 + 2 * j] = p0[j].y + p1[j].y; }
                    sc[0] = (m[0].x + m[1].x) + (m[2].x + m[3].x); sc[1] = (m[0].y + m[1].y) + (m[2].y + m[3].y);
                }
                float mx = fmaxf(fmaxf(fmaxf(sc[2], sc[3]), fmaxf(sc[4], sc[5])), fmaxf(fmaxf(sc[6], sc[7]), fmaxf(sc[8], sc[9])));
                mx = fmaxf(mx, fmaxf(sc[0], sc[1]));
                mx = fmaxf(mx, __shfl_xor_sync(~0u, mx, 1)); mx = fmaxf(mx, __shfl_xor_sync(~0u, mx, 2));
                const float nm = -mx * (SCALE * LOG2E);
#pragma unroll
                for (int i = 0; i < 10; i++) sc[i] = ex2(fmaf(sc[i], SCALE * LOG2E, nm));
                uint32_t p[5];
#pragma unroll
                for (int j = 0; j < 5; j++) p[j] = pack2(sc[2 * j], sc[2 * j + 1]);
                float o[4][4];
#pragma unroll
                for (int i = 0; i < 16; i++) ((float*)o)[i] = 0.f;
#pragma unroll
                for (int n = 0; n < 4; n++) mma8(o[n], p[0], 0u, (n & 1) ? vm[n >> 1].y : vm[n >> 1].x);
#pragma unroll
                for (int n = 0; n < 4; n++) mma16r(o[n], p[1], 0u, p[2], 0u, vb[0][n >> 1][2 * (n & 1)], vb[0][n >> 1][2 * (n & 1) + 1]);
#pragma unroll
                for (int n = 0; n < 4; n++) mma16r(o[n], p[3], 0u, p[4], 0u, vb[1][n >> 1][2 * (n & 1)], vb[1][n >> 1][2 * (n & 1) + 1]);
                float sum = ((sc[0] + sc[1]) + (sc[2] + sc[3])) + ((sc[4] + sc[5]) + (sc[6] + sc[7])) + (sc[8] + sc[9]);
                sum += __shfl_xor_sync(~0u, sum, 1); sum += __shfl_xor_sync(~0u, sum, 2);
                const float inv = rcp(sum);
                sts128(sb + O_OFF + w * 512 + l16,
                       make_uint4(pack2(o[0][0] * inv, o[0][1] * inv), pack2(o[1][0] * inv, o[1][1] * inv),
                                  pack2(o[2][0] * inv, o[2][1] * inv), pack2(o[3][0] * inv, o[3][1] * inv)));
#pragma unroll
                for (int ks = 0; ks < 8; ks++) ldsm4t(wa[ks], wb - 64 * WO_STRIDE + (ks & 3) * 16 * WO_STRIDE + (ks >> 2) * stg_hi);
            }
            {
            FRESH_LANE();
            bar_sync(1, 256);
            TS(5);
            if (pair) {
                float d[4][4];
#pragma unroll
                for (int i = 0; i < 16; i++) ((float*)d)[i] = 0.f;
#pragma unroll
                for (int hf = 0; hf < 2; hf++) {
                    const uint4 o0 = lds128(sb + O_OFF + hf * 1024 + l16), o1 = lds128(sb + O_OFF + hf * 1024 + 512 + l16);
                    mma16(d[0], wa[0], o0.x, o0.y); mma16(d[2], wa[4], o0.x, o0.y);
                    mma16(d[1], wa[1], o0.z, o0.w); mma16(d[3], wa[5], o0.z, o0.w);
                    if (hf == 0) { ldsm4t(wa[0], wb); ldsm4t(wa[4], wb + 32); ldsm4t(wa[1], wb + 16 * WO_STRIDE); ldsm4t(wa[5], wb + 16 * WO_STRIDE + 32); }
                    mma16(d[0], wa[2], o1.x, o1.y); mma16(d[2], wa[6], o1.x, o1.y);
                    mma16(d[1], wa[3], o1.z, o1.w); mma16(d[3], wa[7], o1.z, o1.w);
                    if (hf == 0) {
                        ldsm4t(wa[2], wb + 32 * WO_STRIDE); ldsm4t(wa[6], wb + 32 * WO_STRIDE + 32);
                        ldsm4t(wa[3], wb + 48 * WO_STRIDE); ldsm4t(wa[7], wb + 48 * WO_STRIDE + 32);
                    }
                }
                st_async8(inA, pack2(d[0][0] + d[1][0], d[0][1] + d[1][1]), pack2(d[0][2] + d[1][2], d[0][3] + d[1][3]), mapa(sb + MB_IN + 8 * wA, rA));
                st_async8(inB, pack2(d[2][0] + d[3][0], d[2][1] + d[3][1]), pack2(d[2][2] + d[3][2], d[2][3] + d[3][3]), mapa(sb + MB_IN + 8 * wB, rB));
            } else {
                float d[2][4];
#pragma unroll
                for (int i = 0; i < 8; i++) ((float*)d)[i] = 0.f;
#pragma unroll
                for (int k = 0; k < 4; k++) {
                    const uint4 o0 = lds128(sb + O_OFF + k * 512 + l16);
                    mma16(d[0], wa[2 * k], o0.x, o0.y); mma16(d[1], wa[2 * k + 1], o0.z, o0.w);
                }
                st_async8(inA, pack2(d[0][0] + d[1][0], d[0][1] + d[1][1]), pack2(d[0][2] + d[1][2], d[0][3] + d[1][3]), mapa(sb + MB_IN + 8 * wA, rA));
            }
            }
            TS(6);
            TSV(14, threadIdx.x == 224, clk());
            if (s + 2 < NSEG_) xproj(s + 2);
            TS(7);
        }
        if (warp == 0) { mbar_wait_u(sb + MB_H1, 1); mbar_wait_u(sb + MB_KV + 8, 1); mbar_wait_u(sb + MB_FREE, 1); mbar_wait_u(sb + MB_FREE + 8, 1); if (role == 0) mbar_wait_u(sb + MB_QC, 0); }
        }
        else aux_compute(P, smem, sb, worker, warp);
    } else {
      asm volatile("setmaxnreg.dec.sync.aligned.u32 56;");
      if (warp < 11) {
        const int cw = warp - 8, ct = cw * 32 + lane;
        int idx = (int)rank - 5 * cw; if (idx < 0) idx += nown;
        const bool own = (int)rank < nown && idx < (cw == 2 ? 12 : 14);
        const int T = 14 * cw + idx;
        const bool own2 = own && idx + nown < (cw == 2 ? 12 : 14);
        if (own) st_rel8(&g_X[2][(T * 7 + cl) * 32 + lane], 0u, 0u);
        if (own2) st_rel8(&g_X[2][((T + nown) * 7 + cl) * 32 + lane], 0u, 0u);
        if (is_head) {
            const int nch = role == 2 ? 24 : 28;
            for (int r = cw; r < 128; r += 3) {
                if (lane < nch) cp_async16(sb + WO_OFF + r * WO_STRIDE + lane * 16, Wo + (size_t)(head * 128 + eperm(r)) * DM_ + role * 224 + lane * 8);
            }
            asm volatile("cp.async.commit_group;" ::: "memory");
#pragma unroll 1
            for (int p = ct; p < 1280; p += 96) {
                const int ks = p >> 5, l = p & 31;
                const uint32_t* mp = (const uint32_t*)(mem0 + (l >> 2) * DM_ + ks * 16 + 2 * (l & 3));
                sts64(sb + M_OFF + p * 8, __ldg(mp), __ldg(mp + 4));
            }
            asm volatile("cp.async.wait_all;" ::: "memory");
        }
        __threadfence();
        bar_sync(6, 96);
        if (is_head && lane == 0) mbar_arrive(sb + MB_M + 8 * cw);
        const bool sender = is_head && cw == 2;
        auto send_x = [&](int n) {
            const int st = n & 1;
            mbar_wait_u(sb + MB_XD + 8 * st, (n >> 1) & 1);
            if (n >= 1) mbar_wait_u(sb + MB_H1, (n - 1) & 1);
            if (n >= 2) mbar_wait_u(sb + MB_FREE + 8 * st, ((n - 2) >> 1) & 1);
            const int a0 = (2 * n) % 3, a1 = (2 * n + 1) % 3;
            const uint32_t mbkv = sb + MB_KV + 8 * st, qs = sb + (st ? EX2_OFF : EX_OFF);
            if (lane == 0) {
                if (role == 0) {
                    if (a0 != 0) bulk_s2s(mapa(sb + QX_OFF + st * QX_BYTES, tb + a0), qs, QX_BYTES, mapa(mbkv, tb + a0));
                    if (a1 != 0) bulk_s2s(mapa(sb + QX_OFF + st * QX_BYTES, tb + a1), qs + QX_BYTES, QX_BYTES, mapa(mbkv, tb + a1));
                } else {
                    const uint32_t src = sb + kv_off(role, role, n), dst = sb + kv_off(role, 0, n);
                    bulk_s2s(mapa(dst, tb), src, XB_BYTES, mapa(mbkv, tb));
                    bulk_s2s(mapa(dst, tb + 3 - role), src, XB_BYTES, mapa(mbkv, tb + 3 - role));
                }
            }
            if (role == 0 && (a0 == 0 || a1 == 0)) {
                const uint32_t src = qs + (a0 == 0 ? 0 : QX_BYTES);
                for (int i = lane; i < QX_BYTES / 16; i += 32) sts128(sb + QX_OFF + st * QX_BYTES + i * 16, lds128(src + i * 16));
            }
            __syncwarp();
            if (lane == 0) mbar_expect(mbkv, (role == 0 ? 2 * XB_BYTES : XB_BYTES) + (role != 0 && (a0 == role || a1 == role) ? QX_BYTES : 0));
            __syncwarp();
        };
        if (sender) send_x(0);
        auto owner_loop = [&](auto ntc) {
            constexpr int NT = decltype(ntc)::value;
            const uint32_t mdst = sb + M_OFF + T * 256 + lane * 8;
            const uint32_t mbar = sb + MB_M + 8 * cw;
            if (own && lane == 0) mbar_expect(sb + MB_IN + 8 * cw, NT * nh * 256);
#pragma unroll 1
            for (int s = 0; s < NSEG_ - 1; s++) {
                if (sender) send_x(s + 1);
                if (!own) continue;
                int lane_o = lane;
                asm volatile("" : "+r"(lane_o));
                uint2* xs = &g_X[s & 3][T * 7 * 32 + lane_o];
                uint2* xw = xs + cl * 32;
                const uint32_t ib = sb + IN_OFF + cw * 2560 + lane_o * 8;
                asm volatile("" ::"l"(xw), "r"(ib));
                mbar_wait_u(sb + MB_IN + 8 * cw, s & 1);
                TS(10);
                uint2 v[NT][7];
#pragma unroll
                for (int u = 0; u < NT; u++) {
                    uint2 q[5];
#pragma unroll
                    for (int h = 0; h < 4; h++) q[h] = lds64(ib + u * 1280 + h * 256);
                    q[4] = make_uint2(0, 0);
                    if (NT == 1 && nh == 5) q[4] = lds64(ib + 1024);
#define SUM5(f, c) ((f(q[0].c) + f(q[1].c)) + (f(q[2].c) + f(q[3].c)) + f(q[4].c))
                    const uint32_t o0 = nzw(pack2(SUM5(bflo, x), SUM5(bfhi, x))), o1 = nzw(pack2(SUM5(bflo, y), SUM5(bfhi, y)));
                    st_rel8(xw + u * (12 * 7 * 32), o0, o1);
#pragma unroll
                    for (int c = 0; c < 7; c++) v[u][c] = c == cl ? make_uint2(o0, o1) : make_uint2(0, 0);
                }
                const int tw = clk();
                TS(11);
                if (lane == 0) mbar_expect(sb + MB_IN + 8 * cw, NT * nh * 256);
                while (clk() - tw < DELAY_X) {}
                int guard = 0;
                while (true) {
                    uint32_t chk = 0xffffffffu;
#pragma unroll
                    for (int u = 0; u < NT; u++)
#pragma unroll
                        for (int c = 0; c < 7; c++) if (min(v[u][c].x, v[u][c].y) == 0) v[u][c] = ld_poll8(xs + u * (12 * 7 * 32) + c * 32);
#pragma unroll
                    for (int u = 0; u < NT; u++)
#pragma unroll
                        for (int c = 0; c < 7; c++) chk = min(chk, min(v[u][c].x, v[u][c].y));
                    if (!__any_sync(~0u, chk == 0)) break;
                    if (++guard > SPIN_LIMIT) { g_misc[2] = 2; break; }
                }
                TS(12);
#pragma unroll
                for (int u = 0; u < NT; u++) {
#define SUM7(f, c) (((f(v[u][0].c) + f(v[u][1].c)) + (f(v[u][2].c) + f(v[u][3].c))) + ((f(v[u][4].c) + f(v[u][5].c)) + f(v[u][6].c)))
                    const uint32_t b0 = movm(pack2(SUM7(bflo, x), SUM7(bfhi, x))), b1 = movm(pack2(SUM7(bflo, y), SUM7(bfhi, y)));
                    int d = idx;
#pragma unroll
                    for (int r = 0; r < (NT == 2 ? 12 : 15); r++) {
                        if (r < 12 || nh == 5) st_async8(mapa(mdst + u * (12 * 256), d), b0, b1, mapa(mbar, d));
                        d = d + 1 == nown ? 0 : d + 1;
                    }
                }
                TS(13);
                TSV(15, threadIdx.x == 256, guard);
                if (s > 0) {
#pragma unroll
                    for (int u = 0; u < NT; u++) st_rel8(&g_X[(s - 1) & 3][((T + 12 * u) * 7 + cl) * 32 + lane_o], 0u, 0u);
                    __threadfence();
                }
            }
        };
        if (own2) owner_loop(std::integral_constant<int, 2>());
        else if (own || sender) owner_loop(std::integral_constant<int, 1>());
      } else if (is_head) {
        unsigned* cnt = &g_oxcnt[cl];
        int pending = -1;
#pragma unroll 1
        for (int task = role; task < 2 * NSEG_; task += 3) {
            const int s = task >> 1, mt = task & 1;
            const int st = s & 1;
            mbar_wait_u(sb + MB_KV + 8 * st, (s >> 1) & 1);
            mbar_wait_u(sb + MB_H1, st);
            TS(8);
            int lane = threadIdx.x & 31;
            asm volatile("" : "+r"(lane));
            const int g = lane >> 2, t = lane & 3;
            float sc[5][4];
#pragma unroll
            for (int i = 0; i < 20; i++) ((float*)sc)[i] = 0.f;
            const uint32_t r8 = (lane & 7) * KV_STRIDE;
            {
                const uint32_t qa = sb + QX_OFF + st * QX_BYTES + ((lane >> 3) & 1) * 8 * KV_STRIDE + r8 + (lane >> 4) * 16;
                const uint32_t ka = sb + kv_off(1, role, s) + r8 + ((lane >> 3) & 1) * 16 + (lane >> 4) * 8 * KV_STRIDE;
                const uint32_t kf = sb + KF_OFF + st * 2048 + lane * 8;
                uint32_t a[2][4], b0[2][4], b1[2][4]; uint2 bm[2];
                ldsm4(a[0], qa); bm[0] = lds64(kf); ldsm4(b0[0], ka); ldsm4(b1[0], ka + 16 * KV_STRIDE);
#pragma unroll
                for (int ks = 0; ks < 8; ks++) {
                    const int c = ks & 1, n = c ^ 1;
                    if (ks < 7) {
                        ldsm4(a[n], qa + (ks + 1) * 32); bm[n] = lds64(kf + (ks + 1) * 256);
                        ldsm4(b0[n], ka + (ks + 1) * 32); ldsm4(b1[n], ka + 16 * KV_STRIDE + (ks + 1) * 32);
                    }
                    mma16(sc[0], a[c], bm[c].x, bm[c].y);
                    mma16(sc[1], a[c], b0[c][0], b0[c][1]); mma16(sc[2], a[c], b0[c][2], b0[c][3]);
                    if (mt) { mma16(sc[3], a[c], b1[c][0], b1[c][1]); mma16(sc[4], a[c], b1[c][2], b1[c][3]); }
                }
            }
            if (pending >= 0) { if (lane == 0) red_rel(cnt + pending * 8, 1); pending = -1; __syncwarp(); }
            uint32_t p[5][2];
#pragma unroll
            for (int h = 0; h < 2; h++) {
                const int lim = 8 + 16 * mt + g + 8 * h - 2 * t;
                float mx = -3.0e38f;
#pragma unroll
                for (int j = 0; j < 5; j++) {
                    uint32_t r1 = pack2(sc[j][2 * h], sc[j][2 * h + 1]);
                    r1 = pack2(bflo(r1) * SCALE, bfhi(r1) * SCALE);
                    const float v0 = (8 * j <= lim) ? bflo(r1) : -1.0e9f, v1 = (8 * j + 1 <= lim) ? bfhi(r1) : -1.0e9f;
                    sc[j][2 * h] = v0; sc[j][2 * h + 1] = v1; mx = fmaxf(mx, fmaxf(v0, v1));
                }
                mx = fmaxf(mx, __shfl_xor_sync(~0u, mx, 1)); mx = fmaxf(mx, __shfl_xor_sync(~0u, mx, 2));
                float sum = 0.f;
#pragma unroll
                for (int j = 0; j < 5; j++) {
#pragma unroll
                    for (int i = 0; i < 2; i++) { float e = ex2((sc[j][2 * h + i] - mx) * LOG2E); sc[j][2 * h + i] = e; sum += e; }
                }
                sum += __shfl_xor_sync(~0u, sum, 1); sum += __shfl_xor_sync(~0u, sum, 2);
                const float inv = rcp(sum);
#pragma unroll
                for (int j = 0; j < 5; j++) p[j][h] = pack2(sc[j][2 * h] * inv, sc[j][2 * h + 1] * inv);
            }
            uint32_t* og = (uint32_t*)(g_ox + (size_t)(s * NH_ + head) * 512) + (16 * mt + g) * 32 + t;
            const uint32_t va = sb + kv_off(2, role, s) + r8 + ((lane >> 3) & 1) * 8 * KV_STRIDE + (lane >> 4) * 16;
            const uint32_t vf = sb + VF_OFF + st * 2048 + lane * 8;
            {
                uint32_t b0[2][4], b1[2][4]; uint2 bm[2];
                bm[0] = lds64(vf); ldsm4t(b0[0], va); ldsm4t(b1[0], va + 16 * KV_STRIDE);
#pragma unroll
                for (int np = 0; np < 8; np++) {
                    const int c = np & 1, nx = c ^ 1;
                    if (np < 7) { bm[nx] = lds64(vf + (np + 1) * 256); ldsm4t(b0[nx], va + (np + 1) * 32); ldsm4t(b1[nx], va + 16 * KV_STRIDE + (np + 1) * 32); }
                    float o[2][4] = {{0, 0, 0, 0}, {0, 0, 0, 0}};
                    mma8(o[0], p[0][0], p[0][1], bm[c].x); mma8(o[1], p[0][0], p[0][1], bm[c].y);
                    mma16r(o[0], p[1][0], p[1][1], p[2][0], p[2][1], b0[c][0], b0[c][1]);
                    mma16r(o[1], p[1][0], p[1][1], p[2][0], p[2][1], b0[c][2], b0[c][3]);
                    if (mt) {
                        mma16r(o[0], p[3][0], p[3][1], p[4][0], p[4][1], b1[c][0], b1[c][1]);
                        mma16r(o[1], p[3][0], p[3][1], p[4][0], p[4][1], b1[c][2], b1[c][3]);
                    }
#pragma unroll
                    for (int n = 0; n < 2; n++) {
                        const int ch = (2 * np + n) & 7;
                        int gx = g; asm volatile("" : "+r"(gx));
                        uint32_t* o2 = og + (np >> 2) * 1024 + ((ch ^ gx) << 2);
                        o2[0] = pack2(o[n][0], o[n][1]);
                        o2[256] = pack2(o[n][2], o[n][3]);
                    }
                }
            }
            __syncwarp();
            if (lane < 3) asm volatile("mbarrier.arrive.relaxed.cluster.shared::cluster.b64 _, [%0];" ::"r"(mapa(sb + MB_FREE + 8 * st, tb + lane)) : "memory");
            if (mt == 0 && task + 3 < 2 * NSEG_) pending = s;
            else if (lane == 0) red_rel(cnt + s * 8, 1);
            __syncwarp();
            TS(9);
        }
      }
      else if (lane == 0) aux_control(sb, worker);
    }
    __syncthreads();
    CAL(blockIdx.x, 1);
    cluster_sync();
}

typedef CUresult (*EncodeFn)(CUtensorMap*, CUtensorMapDataType, cuuint32_t, void*, const cuuint64_t*, const cuuint64_t*,
                             const cuuint32_t*, const cuuint32_t*, CUtensorMapInterleave, CUtensorMapSwizzle,
                             CUtensorMapL2promotion, CUtensorMapFloatOOBfill);

extern "C" void kernel_launch(void* const* d_in, const int* in_sizes, int n_in, void* d_out, int out_size) {
    const bf16* x = (const bf16*)d_in[0];
    const bf16* mem0 = (const bf16*)d_in[1];
    const bf16* Wq = (const bf16*)d_in[2];
    const bf16* Wk = (const bf16*)d_in[3];
    const bf16* Wv = (const bf16*)d_in[4];
    const bf16* Wo = (const bf16*)d_in[5];
    const bf16* Bk = (const bf16*)d_in[8];
    const bf16* Bv = (const bf16*)d_in[9];
    const bf16* shk = (const bf16*)d_in[10];
    const bf16* ssmk = (const bf16*)d_in[11];
    const bf16* ssmD = (const bf16*)d_in[12];
    const bf16* gatew = (const bf16*)d_in[13];

    static EncodeFn enc = nullptr;
    if (!enc) {
        void* fn = nullptr; cudaDriverEntryPointQueryResult qr;
        cudaGetDriverEntryPoint("cuTensorMapEncodeTiled", &fn, cudaEnableDefault, &qr);
        enc = (EncodeFn)fn;
        cudaFuncSetAttribute(rec_kernel, cudaFuncAttributeMaxDynamicSharedMemorySize, A_SMEM + 1024);
        cudaFuncSetAttribute(rec_kernel, cudaFuncAttributeNonPortableClusterSizeAllowed, 1);
        cudaFuncSetAttribute(aux_kernel, cudaFuncAttributeMaxDynamicSharedMemorySize, B_SMEM);
    }
    CUtensorMap tmx;
    {
        cuuint64_t dims[3] = {64, (cuuint64_t)S_, 10};
        cuuint64_t strides[2] = {DM_ * 2, 128};
        cuuint32_t box[3] = {64, 32, 1}, es[3] = {1, 1, 1};
        enc(&tmx, CU_TENSOR_MAP_DATA_TYPE_BFLOAT16, 3, (void*)x, dims, strides, box, es, CU_TENSOR_MAP_INTERLEAVE_NONE,
            CU_TENSOR_MAP_SWIZZLE_128B, CU_TENSOR_MAP_L2_PROMOTION_L2_256B, CU_TENSOR_MAP_FLOAT_OOB_FILL_NONE);
    }
    cudaStream_t st = cudaStreamPerThread;
    AuxArgs P = {x, Wo, Bk, Bv, shk, ssmk, ssmD, gatew, (bf16*)d_out};
    {
        cudaLaunchConfig_t ca = {};
        ca.gridDim = dim3(A_CTAS); ca.blockDim = dim3(A_THREADS); ca.dynamicSmemBytes = A_SMEM + 1024; ca.stream = st;
        cudaLaunchAttribute aa[1];
        aa[0].id = cudaLaunchAttributeClusterDimension; aa[0].val.clusterDim.x = 16; aa[0].val.clusterDim.y = 1; aa[0].val.clusterDim.z = 1;
        ca.attrs = aa; ca.numAttrs = 1;
        cudaLaunchKernelEx(&ca, rec_kernel, tmx, mem0, Wq, Wk, Wv, Wo, P);
    }
    cudaLaunchConfig_t cfg = {};
    cfg.gridDim = dim3(NB_CTAS - N_SPARE);
    cfg.blockDim = dim3(B_THREADS); cfg.dynamicSmemBytes = B_SMEM; cfg.stream = st;
    cudaLaunchAttribute at[1];
    at[0].id = cudaLaunchAttributeProgrammaticStreamSerialization; at[0].val.programmaticStreamSerializationAllowed = 1;
    cfg.attrs = at; cfg.numAttrs = 1;
    cudaLaunchKernelEx(&cfg, aux_kernel, P);
}
```

```cpp
#include <cuda_runtime.h>
#include <cuda_bf16.h>
#include <cuda.h>
#include <stdint.h>
#include <type_traits>

typedef __nv_bfloat16 bf16;

constexpr int S_ = 2048, DM_ = 640, NH_ = 32, NSEG_ = 64;
constexpr int NKG_ = 7, NCR_ = 5, NB_CTAS = NKG_ * NCR_;

#define DELAY_X 200
#define SPIN_LIMIT (1 << 13)
#define SPIN_FAIL(guard, code) (((++guard) & 1023) == 0 && (guard >= SPIN_LIMIT || *(volatile unsigned*)&g_misc[2] != 0) && ((g_misc[2] = (code)), true))

__device__ uint2 g_X[4][40 * 7 * 32];
__device__ uint4 g_ox[(size_t)NSEG_ * NH_ * 512];
__device__ float g_part[(size_t)NKG_ * S_ * DM_];
__device__ bf16 g_b[(size_t)S_ * DM_];
__device__ float g_gate[S_];
__device__ unsigned g_oxcnt[NSEG_ * 8];
__device__ unsigned g_pcnt[NSEG_ * 8];
__device__ unsigned g_misc[4];
#define CAL(b, i) do {} while (0)

__device__ __forceinline__ uint32_t smem_u32(const void* p) { return (uint32_t)__cvta_generic_to_shared(p); }
__device__ __forceinline__ void mbar_init(uint32_t mb, int cnt) { asm volatile("mbarrier.init.shared.b64 [%0], %1;" ::"r"(mb), "r"(cnt)); }
__device__ __forceinline__ void mbar_expect(uint32_t mb, int bytes) { asm volatile("mbarrier.arrive.expect_tx.shared.b64 _, [%0], %1;" ::"r"(mb), "r"(bytes) : "memory"); }
__device__ __forceinline__ void mbar_arrive(uint32_t mb) { asm volatile("mbarrier.arrive.shared.b64 _, [%0];" ::"r"(mb) : "memory"); }
__device__ __forceinline__ bool mbar_try(uint32_t mb, int parity) {
    uint32_t ok;
    asm volatile("{ .reg .pred p; mbarrier.try_wait.parity.shared.b64 p, [%1], %2; selp.u32 %0, 1, 0, p; }" : "=r"(ok) : "r"(mb), "r"(parity) : "memory");
    return ok;
}
__device__ __forceinline__ void mbar_wait(uint32_t mb, int parity) {
    int guard = 0;
    while (!mbar_try(mb, parity)) { if (SPIN_FAIL(guard, 1)) break; }
}
__device__ __forceinline__ void mbar_wait_u(uint32_t mb, int parity) {
    asm volatile("{ .reg .pred p; .reg .u32 c; mov.u32 c, 0;\n"
                 "WL%=: mbarrier.try_wait.parity.shared.b64 p, [%0], %1;\n"
                 "@p bra.uni WD%=;\n"
                 "add.u32 c, c, 1; setp.lt.u32 p, c, 16384;\n"
                 "@p bra.uni WL%=;\n"
                 "WD%=: }" ::"r"(mb), "r"(parity) : "memory");
}
__device__ __forceinline__ uint32_t movm(uint32_t a) { uint32_t d; asm volatile("movmatrix.sync.aligned.m8n8.trans.b16 %0, %1;" : "=r"(d) : "r"(a)); return d; }
__device__ __forceinline__ float ex2(float x) { float y; asm("ex2.approx.ftz.f32 %0, %1;" : "=f"(y) : "f"(x)); return y; }
__device__ __forceinline__ float rcp(float x) { float y; asm("rcp.approx.ftz.f32 %0, %1;" : "=f"(y) : "f"(x)); return y; }
__device__ __forceinline__ uint32_t mapa(uint32_t a, uint32_t r) { uint32_t o; asm volatile("mapa.shared::cluster.u32 %0, %1, %2;" : "=r"(o) : "r"(a), "r"(r)); return o; }
__device__ __forceinline__ uint4 ld_poll16(const void* p) { uint4 v; asm volatile("ld.relaxed.gpu.global.v4.u32 {%0,%1,%2,%3}, [%4];" : "=r"(v.x), "=r"(v.y), "=r"(v.z), "=r"(v.w) : "l"(p) : "memory"); return v; }
__device__ __forceinline__ void st_rel16(void* p, uint4 v) { asm volatile("st.relaxed.gpu.global.v4.u32 [%0], {%1,%2,%3,%4};" ::"l"(p), "r"(v.x), "r"(v.y), "r"(v.z), "r"(v.w) : "memory"); }
__device__ __forceinline__ void st_rel4(void* p, uint32_t v) { asm volatile("st.relaxed.gpu.global.u32 [%0], %1;" ::"l"(p), "r"(v) : "memory"); }
__device__ __forceinline__ unsigned ld_acq(const unsigned* p) { unsigned v; asm volatile("ld.acquire.gpu.global.u32 %0, [%1];" : "=r"(v) : "l"(p) : "memory"); return v; }
__device__ __forceinline__ void red_rel(unsigned* p, unsigned v) { asm volatile("red.release.gpu.global.add.u32 [%0], %1;" ::"l"(p), "r"(v) : "memory"); }
__device__ __forceinline__ void bar_sync(int id, int n) { asm volatile("bar.sync %0, %1;" ::"r"(id), "r"(n) : "memory"); }
__device__ __forceinline__ void st_async8(uint32_t dst, uint32_t a, uint32_t b, uint32_t mb) {
    asm volatile("st.async.weak.shared::cluster.mbarrier::complete_tx::bytes.v2.b32 [%0], {%1,%2}, [%3];" ::"r"(dst), "r"(a), "r"(b), "r"(mb) : "memory");
}
__device__ __forceinline__ void st_async16(uint32_t dst, uint32_t a, uint32_t b, uint32_t c, uint32_t d, uint32_t mb) {
    asm volatile("st.async.weak.shared::cluster.mbarrier::complete_tx::bytes.v4.b32 [%0], {%1,%2,%3,%4}, [%5];" ::"r"(dst), "r"(a), "r"(b), "r"(c), "r"(d), "r"(mb) : "memory");
}
__device__ __forceinline__ uint2 lds64(uint32_t a) { uint2 v; asm volatile("ld.shared.v2.u32 {%0,%1}, [%2];" : "=r"(v.x), "=r"(v.y) : "r"(a) : "memory"); return v; }
__device__ __forceinline__ uint2 ld_poll8(const void* p) { uint2 v; asm volatile("ld.relaxed.gpu.global.v2.u32 {%0,%1}, [%2];" : "=r"(v.x), "=r"(v.y) : "l"(p) : "memory"); return v; }
__device__ __forceinline__ void bulk_s2s(uint32_t dst, uint32_t src, uint32_t bytes, uint32_t mb) {
    asm volatile("cp.async.bulk.shared::cluster.shared::cta.mbarrier::complete_tx::bytes [%0], [%1], %2, [%3];" ::"r"(dst), "r"(src), "r"(bytes), "r"(mb) : "memory");
}
__device__ __forceinline__ void bulk_g2s(uint32_t dst, const void* src, uint32_t bytes, uint32_t mb) {
    asm volatile("cp.async.bulk.shared::cluster.global.mbarrier::complete_tx::bytes [%0], [%1], %2, [%3];" ::"r"(dst), "l"(src), "r"(bytes), "r"(mb) : "memory");
}
__device__ __forceinline__ void tma3d(uint32_t dst, const CUtensorMap* tm, int c0, int c1, int c2, uint32_t mb) {
    asm volatile("cp.async.bulk.tensor.3d.shared::cluster.global.mbarrier::complete_tx::bytes [%0], [%1, {%3, %4, %5}], [%2];"
                 ::"r"(dst), "l"((uint64_t)tm), "r"(mb), "r"(c0), "r"(c1), "r"(c2) : "memory");
}
__device__ __forceinline__ void tma3d_mc(uint32_t dst, const CUtensorMap* tm, int c0, int c1, int c2, uint32_t mb, uint16_t mask) {
    asm volatile("cp.async.bulk.tensor.3d.shared::cluster.global.mbarrier::complete_tx::bytes.multicast::cluster [%0], [%1, {%3, %4, %5}], [%2], %6;"
                 ::"r"(dst), "l"((uint64_t)tm), "r"(mb), "r"(c0), "r"(c1), "r"(c2), "h"(mask) : "memory");
}
__device__ __forceinline__ void st_rel8(void* p, uint32_t a, uint32_t b) { asm volatile("st.relaxed.gpu.global.v2.u32 [%0], {%1,%2};" ::"l"(p), "r"(a), "r"(b) : "memory"); }
__device__ __forceinline__ void fence_async_smem() { asm volatile("fence.proxy.async.shared::cta;" ::: "memory"); }
__device__ __forceinline__ void fence_async_all() { asm volatile("fence.proxy.async;" ::: "memory"); }
__device__ __forceinline__ void cp_async16(uint32_t dst, const void* src) { asm volatile("cp.async.cg.shared.global [%0], [%1], 16;" ::"r"(dst), "l"(src) : "memory"); }
__device__ __forceinline__ void cluster_sync() { asm volatile("barrier.cluster.arrive.aligned; barrier.cluster.wait.aligned;" ::: "memory"); }
__device__ __forceinline__ int clk() { int c; asm volatile("mov.u32 %0, %%clock;" : "=r"(c)); return c; }

__device__ __forceinline__ void ldsm4(uint32_t* r, uint32_t a) { asm volatile("ldmatrix.sync.aligned.m8n8.x4.shared.b16 {%0,%1,%2,%3}, [%4];" : "=r"(r[0]), "=r"(r[1]), "=r"(r[2]), "=r"(r[3]) : "r"(a) : "memory"); }
__device__ __forceinline__ void ldsm2(uint32_t* r, uint32_t a) { asm volatile("ldmatrix.sync.aligned.m8n8.x2.shared.b16 {%0,%1}, [%2];" : "=r"(r[0]), "=r"(r[1]) : "r"(a) : "memory"); }
__device__ __forceinline__ void ldsm4t(uint32_t* r, uint32_t a) { asm volatile("ldmatrix.sync.aligned.m8n8.x4.trans.shared.b16 {%0,%1,%2,%3}, [%4];" : "=r"(r[0]), "=r"(r[1]), "=r"(r[2]), "=r"(r[3]) : "r"(a) : "memory"); }
__device__ __forceinline__ void ldsm2t(uint32_t* r, uint32_t a) { asm volatile("ldmatrix.sync.aligned.m8n8.x2.trans.shared.b16 {%0,%1}, [%2];" : "=r"(r[0]), "=r"(r[1]) : "r"(a) : "memory"); }
__device__ __forceinline__ void stsm4t(uint32_t a, uint32_t r0, uint32_t r1, uint32_t r2, uint32_t r3) {
    asm volatile("stmatrix.sync.aligned.m8n8.x4.trans.shared.b16 [%0], {%1,%2,%3,%4};" ::"r"(a), "r"(r0), "r"(r1), "r"(r2), "r"(r3) : "memory");
}
__device__ __forceinline__ uint4 lds128(uint32_t a) { uint4 v; asm volatile("ld.shared.v4.u32 {%0,%1,%2,%3}, [%4];" : "=r"(v.x), "=r"(v.y), "=r"(v.z), "=r"(v.w) : "r"(a) : "memory"); return v; }
__device__ __forceinline__ float2 lds64f(uint32_t a) { float2 v; asm volatile("ld.shared.v2.f32 {%0,%1}, [%2];" : "=f"(v.x), "=f"(v.y) : "r"(a) : "memory"); return v; }
__device__ __forceinline__ float lds32f(uint32_t a) { float v; asm volatile("ld.shared.f32 %0, [%1];" : "=f"(v) : "r"(a) : "memory"); return v; }
__device__ __forceinline__ uint32_t lds32(uint32_t a) { uint32_t v; asm volatile("ld.shared.u32 %0, [%1];" : "=r"(v) : "r"(a) : "memory"); return v; }
__device__ __forceinline__ void sts128(uint32_t a, uint4 v) { asm volatile("st.shared.v4.u32 [%0], {%1,%2,%3,%4};" ::"r"(a), "r"(v.x), "r"(v.y), "r"(v.z), "r"(v.w) : "memory"); }
__device__ __forceinline__ void sts128f(uint32_t a, float x, float y, float z, float w) { asm volatile("st.shared.v4.f32 [%0], {%1,%2,%3,%4};" ::"r"(a), "f"(x), "f"(y), "f"(z), "f"(w) : "memory"); }
__device__ __forceinline__ void sts64f(uint32_t a, float x, float y) { asm volatile("st.shared.v2.f32 [%0], {%1,%2};" ::"r"(a), "f"(x), "f"(y) : "memory"); }
__device__ __forceinline__ void sts64(uint32_t a, uint32_t x, uint32_t y) { asm volatile("st.shared.v2.u32 [%0], {%1,%2};" ::"r"(a), "r"(x), "r"(y) : "memory"); }
__device__ __forceinline__ void sts32f(uint32_t a, float x) { asm volatile("st.shared.f32 [%0], %1;" ::"r"(a), "f"(x) : "memory"); }

__device__ __forceinline__ void mma16(float* d, const uint32_t* a, uint32_t b0, uint32_t b1) {
    asm volatile("mma.sync.aligned.m16n8k16.row.col.f32.bf16.bf16.f32 {%0,%1,%2,%3}, {%4,%5,%6,%7}, {%8,%9}, {%0,%1,%2,%3};"
                 : "+f"(d[0]), "+f"(d[1]), "+f"(d[2]), "+f"(d[3]) : "r"(a[0]), "r"(a[1]), "r"(a[2]), "r"(a[3]), "r"(b0), "r"(b1));
}
__device__ __forceinline__ void mma16r(float* d, uint32_t a0, uint32_t a1, uint32_t a2, uint32_t a3, uint32_t b0, uint32_t b1) {
    asm volatile("mma.sync.aligned.m16n8k16.row.col.f32.bf16.bf16.f32 {%0,%1,%2,%3}, {%4,%5,%6,%7}, {%8,%9}, {%0,%1,%2,%3};"
                 : "+f"(d[0]), "+f"(d[1]), "+f"(d[2]), "+f"(d[3]) : "r"(a0), "r"(a1), "r"(a2), "r"(a3), "r"(b0), "r"(b1));
}
__device__ __forceinline__ void mma8(float* d, uint32_t a0, uint32_t a1, uint32_t b0) {
    asm volatile("mma.sync.aligned.m16n8k8.row.col.f32.bf16.bf16.f32 {%0,%1,%2,%3}, {%4,%5}, {%6}, {%0,%1,%2,%3};"
                 : "+f"(d[0]), "+f"(d[1]), "+f"(d[2]), "+f"(d[3]) : "r"(a0), "r"(a1), "r"(b0));
}
__device__ __forceinline__ void wgmma_n32(float* d, const uint32_t* a, uint32_t desc_lo, int sc) {
    asm volatile("{ .reg .pred p; .reg .b64 dd; setp.ne.b32 p, %21, 0; mov.b64 dd, {%20, 0x40000040};\n"
                 "wgmma.mma_async.sync.aligned.m64n32k16.f32.bf16.bf16 {%0,%1,%2,%3,%4,%5,%6,%7,%8,%9,%10,%11,%12,%13,%14,%15}, {%16,%17,%18,%19}, dd, p, 1, 1, 0; }\n"
                 : "+f"(d[0]), "+f"(d[1]), "+f"(d[2]), "+f"(d[3]), "+f"(d[4]), "+f"(d[5]), "+f"(d[6]), "+f"(d[7]),
                   "+f"(d[8]), "+f"(d[9]), "+f"(d[10]), "+f"(d[11]), "+f"(d[12]), "+f"(d[13]), "+f"(d[14]), "+f"(d[15])
                 : "r"(a[0]), "r"(a[1]), "r"(a[2]), "r"(a[3]), "r"(desc_lo), "r"(sc));
}
#define WG_FENCE() asm volatile("wgmma.fence.sync.aligned;" ::: "memory")
#define WG_COMMIT() asm volatile("wgmma.commit_group.sync.aligned;" ::: "memory")
#define WG_WAIT0() asm volatile("wgmma.wait_group.sync.aligned 0;" ::: "memory")
__device__ __forceinline__ uint32_t desc_sw128(uint32_t saddr) { return ((saddr & 0x3FFFF) >> 4) | (1u << 16); }
__device__ __forceinline__ uint32_t pack2(float lo, float hi) { __nv_bfloat162 h = __floats2bfloat162_rn(lo, hi); return *(uint32_t*)&h; }
__device__ __forceinline__ float bflo(uint32_t u) { return __uint_as_float(u << 16); }
__device__ __forceinline__ float bfhi(uint32_t u) { return __uint_as_float(u & 0xffff0000u); }
__device__ __forceinline__ float rbf(float x) { return __uint_as_float(pack2(0.f, x)); }
__device__ __forceinline__ uint32_t nzw(uint32_t u) { return u == 0 ? 0x80008000u : u; }
__device__ __forceinline__ uint32_t min4(uint4 v) { return min(min(v.x, v.y), min(v.z, v.w)); }
__device__ __forceinline__ void mbar_arrive_if(uint32_t mb, uint32_t c) {
    asm volatile("{ .reg .pred p; setp.ne.u32 p, %1, 0; @p mbarrier.arrive.shared.b64 _, [%0]; }" ::"r"(mb), "r"(c) : "memory");
}
__device__ __forceinline__ int eperm(int p) { return (p & ~15) + 2 * (p & 7) + ((p >> 3) & 1); }

constexpr int U_STRIDE = 136 * 48;
constexpr int KR_STRIDE = 2080 * 2 * 2;
constexpr int B_U_OFF = 0, B_KR_OFF = 8 * U_STRIDE, B_CONV_END = B_KR_OFF + 8 * KR_STRIDE;
constexpr int B_OX_STAGES = 3, B_OX_BYTES = 40960;
constexpr int B_BAR_OFF = B_OX_STAGES * B_OX_BYTES;
constexpr int B_SMEM = B_BAR_OFF + 128;

constexpr int B_THREADS = 384;
constexpr int B_LAG = 2;

struct AuxArgs { const bf16 *x, *Wo, *Bk, *Bv, *shk, *ssmk, *ssmD, *gatew; bf16* out; };
constexpr int MBB_FULL = B_BAR_OFF, MBB_EMPTY = B_BAR_OFF + 24, MBB_ST = B_BAR_OFF + 48, MBB_GO = B_BAR_OFF + 80, MBB_FLAG = B_BAR_OFF + 96;

__device__ __forceinline__ void aux_init(uint32_t sb) {
    for (int i = 0; i < B_OX_STAGES; i++) { mbar_init(sb + MBB_FULL + 8 * i, 1); mbar_init(sb + MBB_EMPTY + 8 * i, 8); }
    for (int i = 0; i < 4; i++) mbar_init(sb + MBB_ST + 8 * i, 8);
    mbar_init(sb + MBB_GO, 8);
    fence_async_smem();
}
__device__ __forceinline__ bool mbar_test(uint32_t mb, int parity) {
    uint32_t ok;
    asm volatile("{ .reg .pred p; mbarrier.test_wait.parity.shared.b64 p, [%1], %2; selp.u32 %0, 1, 0, p; }" : "=r"(ok) : "r"(mb), "r"(parity) : "memory");
    return ok;
}
__device__ __forceinline__ void aux_control(uint32_t sb, int cta) {
    const int kg = cta / NCR_, cr = cta % NCR_;
    const int h0 = kg < 4 ? kg * 5 : 20 + (kg - 4) * 4, nh = kg < 4 ? 5 : 4;
    { int guard = 0; while (!mbar_try(sb + MBB_GO, 0)) { if (++guard > (1 << 22)) break; } }
    red_rel(&g_misc[0], 1);
    int nl = 0, nr = 0, guard = 0;
    while (nr < NSEG_) {
        bool did = false;
        if (nl < NSEG_) {
            const int st = nl % B_OX_STAGES;
            if ((nl < B_OX_STAGES || mbar_test(sb + MBB_EMPTY + 8 * st, (nl / B_OX_STAGES - 1) & 1)) &&
                ld_acq(&g_oxcnt[nl * 8 + kg]) >= (unsigned)(2 * nh)) {
                fence_async_all();
                mbar_expect(sb + MBB_FULL + 8 * st, nh * 8192);
                bulk_g2s(sb + st * B_OX_BYTES, g_ox + (size_t)(nl * NH_ + h0) * 512, nh * 8192, sb + MBB_FULL + 8 * st);
                nl++; did = true;
            }
        }
        if (nr < nl && mbar_test(sb + MBB_ST + 8 * (nr & 3), (nr >> 2) & 1)) { red_rel(&g_pcnt[nr * 8 + cr], 1); nr++; did = true; }
        if (did) guard = 0;
        else { if (++guard > (1 << 17)) { g_misc[2] = 4; break; } __nanosleep(100); }
    }
}
__device__ __forceinline__ void aux_compute(const AuxArgs& P, unsigned char* smem, uint32_t sb, int cta, int warp) {
    const bf16* __restrict__ x = P.x; const bf16* __restrict__ Wo = P.Wo; const bf16* __restrict__ Bk = P.Bk; const bf16* __restrict__ Bv = P.Bv;
    const bf16* __restrict__ shk = P.shk; const bf16* __restrict__ ssmk = P.ssmk; const bf16* __restrict__ ssmD = P.ssmD;
    const bf16* __restrict__ gatew = P.gatew; bf16* __restrict__ out = P.out;
    const int tid = threadIdx.x, lane = tid & 31;
    const int g = lane >> 2, t = lane & 3;
    const int kg = cta / NCR_, cr = cta % NCR_;
    const int h0 = kg < 4 ? kg * 5 : 20 + (kg - 4) * 4, nh = kg < 4 ? 5 : 4;
    const uint32_t mb_full = sb + MBB_FULL, mb_empty = sb + MBB_EMPTY, mb_st = sb + MBB_ST, mb_go = sb + MBB_GO;
    CAL(112 + cta, 0);
    {
        uint32_t wv[10];
#pragma unroll
        for (int i = 0; i < 10; i++) wv[i] = __ldg((const uint32_t*)gatew + lane + 32 * i);
        uint32_t xv[8][10];
#pragma unroll
        for (int j = 0; j < 8; j++) {
            const int r = min(cta * 8 + warp + j * (NB_CTAS * 8), S_ - 1);
#pragma unroll
            for (int i = 0; i < 10; i++) xv[j][i] = __ldg((const uint32_t*)(x + (size_t)r * DM_) + lane + 32 * i);
        }
#pragma unroll
        for (int j = 0; j < 8; j++) {
            const int r = cta * 8 + warp + j * (NB_CTAS * 8);
            float acc = 0.f;
#pragma unroll
            for (int i = 0; i < 10; i++) acc += rbf(bflo(xv[j][i]) * bflo(wv[i])) + rbf(bfhi(xv[j][i]) * bfhi(wv[i]));
#pragma unroll
            for (int o = 16; o; o >>= 1) acc += __shfl_xor_sync(~0u, acc, o);
            if (lane == 0 && r < S_) g_gate[r] = rbf(1.f / (1.f + __expf(-rbf(acc))));
        }
    }

    for (int item = (cta + 19) % NB_CTAS; item < 80; item += NB_CTAS) {
        const int c0 = item * 8;
        bar_sync(1, 256);
        for (int i = tid; i < 8 * 24; i += 256) sts128(sb + B_U_OFF + (i / 24) * U_STRIDE + (i % 24) * 16, make_uint4(0, 0, 0, 0));
        {
            const uint32_t krb = sb + B_KR_OFF + warp * KR_STRIDE;
            const bf16* kp = ssmk + (size_t)(c0 + warp) * S_;
            uint4 v[8]; uint32_t pv[8];
#pragma unroll
            for (int j = 0; j < 8; j++) {
                const int i = lane + 32 * j;
                v[j] = __ldg((const uint4*)kp + i);
                pv[j] = i > 0 ? __ldg((const uint32_t*)kp + 4 * i - 1) : 0u;
            }
#pragma unroll
            for (int j = 0; j < 8; j++) {
                const int i = lane + 32 * j;
                sts128(krb + (2040 - 8 * i) * 2, make_uint4(__byte_perm(v[j].w, 0, 0x1032), __byte_perm(v[j].z, 0, 0x1032),
                                                            __byte_perm(v[j].y, 0, 0x1032), __byte_perm(v[j].x, 0, 0x1032)));
                sts128(krb + 4160 + (2040 - 8 * i) * 2, make_uint4(__byte_perm(v[j].w, v[j].z, 0x7610), __byte_perm(v[j].z, v[j].y, 0x7610),
                                                                   __byte_perm(v[j].y, v[j].x, 0x7610), __byte_perm(v[j].x, pv[j], 0x7610)));
            }
            if (lane < 4) { sts128(krb + 4096 + lane * 16, make_uint4(0, 0, 0, 0)); sts128(krb + 4160 + 4096 + lane * 16, make_uint4(0, 0, 0, 0)); }
        }
        {
            float sh[8][4];
#pragma unroll
            for (int c = 0; c < 8; c++) {
                uint2 v = __ldg((const uint2*)(shk + (c0 + c) * 4));
                sh[c][0] = bflo(v.x); sh[c][1] = bfhi(v.x); sh[c][2] = bflo(v.y); sh[c][3] = bfhi(v.y);
            }
            const int t0 = tid * 8;
            uint4 kr[11], vr[8];
#pragma unroll
            for (int i = 0; i < 11; i++) { int r = t0 - 3 + i; kr[i] = r >= 0 ? __ldg((const uint4*)(Bk + (size_t)r * DM_ + c0)) : make_uint4(0, 0, 0, 0); }
#pragma unroll
            for (int i = 0; i < 8; i++) vr[i] = __ldg((const uint4*)(Bv + (size_t)(t0 + i) * DM_ + c0));
#pragma unroll
            for (int c = 0; c < 8; c++) {
                float res[8];
#pragma unroll
                for (int i = 0; i < 8; i++) {
                    float a = 0.f;
#pragma unroll
                    for (int tt = 0; tt < 4; tt++) {
                        uint32_t wd = ((const uint32_t*)&kr[i + tt])[c >> 1];
                        float kv_ = (c & 1) ? bfhi(wd) : bflo(wd);
                        a = rbf(a + rbf(kv_ * sh[c][3 - tt]));
                    }
                    uint32_t wd = ((const uint32_t*)&vr[i])[c >> 1];
                    res[i] = a * ((c & 1) ? bfhi(wd) : bflo(wd));
                }
                uint4 o = make_uint4(pack2(res[0], res[1]), pack2(res[2], res[3]), pack2(res[4], res[5]), pack2(res[6], res[7]));
                sts128(sb + B_U_OFF + c * U_STRIDE + (8 + (tid >> 1)) * 48 + (tid & 1) * 16, o);
            }
        }
        bar_sync(1, 256);
        {
            float acc[16][4];
#pragma unroll
            for (int i = 0; i < 64; i++) ((float*)acc)[i] = 0.f;
            const uint32_t kb = sb + B_KR_OFF + warp * KR_STRIDE + ((g & 1) ? (2047 - g + 2 * t) * 2 : 4160 + (2046 - g + 2 * t) * 2);
            const uint32_t ub = sb + B_U_OFF + warp * U_STRIDE + (8 + (lane & 7) + (lane >> 4) * 8) * 48 + ((lane >> 3) & 1) * 16;
#pragma unroll 1
            for (int r = 0; r < 8; r++) {
                uint32_t pa[16][3];
#pragma unroll
                for (int m = 0; m < 16; m++) {
                    const uint32_t a = kb - (16 * (r + 8 * m)) * 2;
                    pa[m][0] = lds32(a + 16); pa[m][1] = lds32(a); pa[m][2] = lds32(a - 16);
                }
#pragma unroll
                for (int d = 0; d < 16; d += 2) {
                    uint32_t b[4];
                    ldsm4(b, ub + (8 * d - r) * 48);
#pragma unroll
                    for (int m = 0; m < 16 - d; m++) mma16r(acc[m + d], pa[m][1], pa[m][2], pa[m][0], pa[m][1], b[0], b[1]);
#pragma unroll
                    for (int m = 0; m < 15 - d; m++) mma16r(acc[m + d + 1], pa[m][1], pa[m][2], pa[m][0], pa[m][1], b[2], b[3]);
                }
            }
            __syncwarp();
            const float Dv = __bfloat162float(ssmD[c0 + warp]);
            bf16* u = (bf16*)(smem + B_U_OFF + warp * U_STRIDE) + 8 * 24;
#pragma unroll
            for (int i = 0; i < 16; i++) {
#pragma unroll
                for (int q = 0; q < 4; q++) {
                    const int idx = (8 * i + 2 * t + (q & 1)) * 24 + g + (q >> 1) * 8;
                    const float kvv = __bfloat162float(u[idx]);
                    u[idx] = __float2bfloat16_rn(rbf(acc[i][q]) + rbf(kvv * Dv));
                }
            }
        }
        uint4 xv[8];
#pragma unroll
        for (int j = 0; j < 8; j++) xv[j] = __ldg((const uint4*)(x + (size_t)(tid + 256 * j) * DM_ + c0));
        bar_sync(1, 256);
#pragma unroll
        for (int j = 0; j < 8; j++) {
            const int r = tid + 256 * j;
            uint32_t o[4];
            const bf16* u = (const bf16*)(smem + B_U_OFF) + (8 + (r >> 4)) * 24 + (r & 15);
#pragma unroll
            for (int c = 0; c < 4; c++) {
                uint32_t wd = ((const uint32_t*)&xv[j])[c];
                o[c] = pack2(bflo(wd) * __bfloat162float(u[(2 * c) * (U_STRIDE / 2)]), bfhi(wd) * __bfloat162float(u[(2 * c + 1) * (U_STRIDE / 2)]));
            }
            *(uint4*)(g_b + (size_t)r * DM_ + c0) = make_uint4(o[0], o[1], o[2], o[3]);
        }
    }
    fence_async_smem();
    __syncwarp();
    if (lane == 0) mbar_arrive(mb_go);
    CAL(112 + cta, 1);

    const int wg = warp >> 2, w = warp & 3;
    const int col = cr * 128 + wg * 64 + 16 * w + 2 * g;
    uint32_t A[40][4];
#pragma unroll
    for (int ks = 0; ks < 40; ks++) {
        const int hh = ks >> 3;
        uint32_t r[4] = {0, 0, 0, 0};
        if (hh < nh) {
#pragma unroll
            for (int i = 0; i < 4; i++) {
                const int p = (ks & 7) * 16 + 2 * t + (i & 1) + (i >> 1) * 8;
                r[i] = __ldg((const uint32_t*)(Wo + (size_t)((h0 + hh) * 128 + eperm(p)) * DM_ + col));
            }
        }
        A[ks][0] = __byte_perm(r[0], r[1], 0x5410); A[ks][1] = __byte_perm(r[0], r[1], 0x7632);
        A[ks][2] = __byte_perm(r[2], r[3], 0x5410); A[ks][3] = __byte_perm(r[2], r[3], 0x7632);
    }
    CAL(112 + cta, 2);
    auto finalize = [&](int n) {
        const int r = kg + 7 * warp;
        if (r < 32) {
            if (lane == 0) {
                int guard = 0;
                while (ld_acq(&g_pcnt[n * 8 + cr]) < (unsigned)NKG_) { if (++guard > (1 << 18)) { g_misc[2] = 6; break; } __nanosleep(50); }
                if (n == 0) { guard = 0; while (ld_acq(&g_misc[0]) < (unsigned)NB_CTAS) { if (++guard > (1 << 22)) break; __nanosleep(200); } }
            }
            __syncwarp();
            const int row = n * 32 + r, c = cr * 128 + lane * 4;
            float4 v[NKG_];
#pragma unroll
            for (int k = 0; k < NKG_; k++) v[k] = __ldcg((const float4*)(g_part + ((size_t)k * S_ + row) * DM_ + c));
            const float gt = __ldcg(&g_gate[row]), og = rbf(1.f - gt);
            const uint2 bv = __ldcg((const uint2*)(g_b + (size_t)row * DM_ + c));
            float4 a = v[0];
#pragma unroll
            for (int k = 1; k < NKG_; k++) { a.x += v[k].x; a.y += v[k].y; a.z += v[k].z; a.w += v[k].w; }
            uint2 o;
            o.x = pack2(rbf(gt * rbf(a.x)) + rbf(og * bflo(bv.x)), rbf(gt * rbf(a.y)) + rbf(og * bfhi(bv.x)));
            o.y = pack2(rbf(gt * rbf(a.z)) + rbf(og * bflo(bv.y)), rbf(gt * rbf(a.w)) + rbf(og * bfhi(bv.y)));
            *(uint2*)(out + (size_t)row * DM_ + c) = o;
        }
    };
#pragma unroll 1
    for (int n = 0; n < NSEG_; n++) {
        const int st = n % B_OX_STAGES;
        { int guard = 0; while (!mbar_try(mb_full + 8 * st, (n / B_OX_STAGES) & 1)) { if (++guard > (1 << 20)) break; } }
        __syncwarp();
        float acc[16];
        const uint32_t d0 = __shfl_sync(0xffffffffu, desc_sw128(sb + st * B_OX_BYTES), 0);
        WG_FENCE();
#pragma unroll
        for (int ks = 0; ks < 32; ks++) wgmma_n32(acc, A[ks], d0 + (((ks >> 2) * 4096 + (ks & 3) * 32) >> 4), ks > 0);
        if (nh == 5) {
#pragma unroll
            for (int ks = 32; ks < 40; ks++) wgmma_n32(acc, A[ks], d0 + (((ks >> 2) * 4096 + (ks & 3) * 32) >> 4), 1);
        }
        WG_COMMIT();
        WG_WAIT0();
        if (lane == 0) mbar_arrive(mb_empty + 8 * st);
        float* pp = g_part + ((size_t)kg * S_ + n * 32) * DM_ + col;
#pragma unroll
        for (int j = 0; j < 4; j++) {
            *(float2*)(pp + (size_t)(8 * j + 2 * t) * DM_) = make_float2(acc[4 * j], acc[4 * j + 2]);
            *(float2*)(pp + (size_t)(8 * j + 2 * t + 1) * DM_) = make_float2(acc[4 * j + 1], acc[4 * j + 3]);
        }
        __syncwarp();
        if (lane == 0) mbar_arrive(mb_st + 8 * (n & 3));
        if (n >= B_LAG) finalize(n - B_LAG);
    }
    for (int n = NSEG_ - B_LAG; n < NSEG_; n++) finalize(n);
    CAL(112 + cta, 3);
    bar_sync(1, 256);
    volatile unsigned* flag = (volatile unsigned*)(smem + MBB_FLAG);
    if (tid == 0) {
        unsigned old; asm volatile("atom.acq_rel.gpu.global.add.u32 %0, [%1], 1;" : "=r"(old) : "l"(&g_misc[1]) : "memory");
        *flag = (old == NB_CTAS - 1);
    }
    bar_sync(1, 256);
    if (*flag) {
        for (int i = tid; i < NSEG_ * 8; i += 256) { g_oxcnt[i] = 0; g_pcnt[i] = 0; }
        if (tid == 0) { g_misc[0] = 0; g_misc[1] = 0; }
    }
}

constexpr int N_SPARE = 16;
__global__ void __launch_bounds__(B_THREADS, 1) aux_kernel(const AuxArgs P) {
    extern __shared__ __align__(1024) unsigned char smem[];
    const uint32_t sb = __shfl_sync(0xffffffffu, smem_u32(smem), 0);
    const int warp = __shfl_sync(0xffffffffu, threadIdx.x >> 5, 0);
    const int cta = N_SPARE + blockIdx.x;
    if (threadIdx.x == 0) aux_init(sb);
    __syncthreads();
    if (warp >= 8) {
        asm volatile("setmaxnreg.dec.sync.aligned.u32 56;");
        if (threadIdx.x == 256) aux_control(sb, cta);
    } else {
        asm volatile("setmaxnreg.inc.sync.aligned.u32 224;");
        aux_compute(P, smem, sb, cta, warp);
    }
}

constexpr int XT_OFF = 0, WO_OFF = 81920, WO_STRIDE = 464, KV_STRIDE = 272, XB_BYTES = 32 * KV_STRIDE, QX_BYTES = 16 * KV_STRIDE,
              K_OFF = 141312, V_OFF = K_OFF + 2 * XB_BYTES, EX_OFF = V_OFF + 2 * XB_BYTES  ,
              QX_OFF = EX_OFF + XB_BYTES, QF_OFF = QX_OFF + 2 * QX_BYTES, KF_OFF = QF_OFF + 2048, VF_OFF = KF_OFF + 4096,
              IN_OFF = VF_OFF + 4096, M_OFF = IN_OFF + 7680, EX2_OFF = M_OFF + 10240 + 512  ,
              BAR_OFF = EX2_OFF + XB_BYTES, A_SMEM = BAR_OFF + 144;
constexpr int O_OFF = QF_OFF;
__device__ __forceinline__ uint32_t kv_off(int which, int role, int n) {
    const int base = which == 1 ? K_OFF : V_OFF;
    if (which != role) return base + (n & 1) * XB_BYTES;
    const int j = n % 3;
    return j == 2 ? EX_OFF : base + j * XB_BYTES;
}
__device__ __forceinline__ void tile_owner(int T, int nown, int& gr, int& rk, int& sl) {
    gr = T >= 28 ? 2 : (T >= 14 ? 1 : 0);
    int i = T - 14 * gr;
    sl = i >= nown; i -= sl * nown;
    const int r = i + 5 * gr;
    rk = r >= nown ? r - nown : r;
}
constexpr int MB_X = BAR_OFF  , MB_M = BAR_OFF + 16  , MB_IN = BAR_OFF + 40  , MB_QC = BAR_OFF + 120, MB_H1 = BAR_OFF + 64,
              MB_KV = BAR_OFF + 72  , MB_FREE = BAR_OFF + 88  , MB_XD = BAR_OFF + 104  , MB_WO = BAR_OFF + 128;
constexpr float SCALE = 0.08838834764831845f;
constexpr float LOG2E = 1.4426950408889634f;
constexpr int A_THREADS = 384, A_CTAS = 112;

#define FRESH_LANE() int lane = lane_r; asm volatile("" : "+r"(lane)); const int g = lane >> 2, t = lane & 3; const uint32_t l16 = lane * 16; (void)g; (void)t; (void)l16
#define PIN(x) asm volatile("" ::"r"(x))
#define TS(i) do {} while (0)
#define TSV(i, cond, val) do {} while (0)

__global__ void __launch_bounds__(A_THREADS, 1)
rec_kernel(const __grid_constant__ CUtensorMap tmx, const bf16* __restrict__ mem0, const bf16* __restrict__ Wq,
           const bf16* __restrict__ Wk, const bf16* __restrict__ Wv, const bf16* __restrict__ Wo, const AuxArgs P) {
    extern __shared__ __align__(1024) unsigned char smem[];
    const uint32_t sb = __shfl_sync(0xffffffffu, smem_u32(smem), 0);
    const int tid = threadIdx.x, warp = __shfl_sync(0xffffffffu, tid >> 5, 0);
    const int lane = tid & 31;
    const int g = lane >> 2, t = lane & 3;
    uint32_t rank; asm volatile("mov.u32 %0, %%cluster_ctarank;" : "=r"(rank));
    const int cl = blockIdx.x >> 4;
    const int nh = cl < 4 ? 5 : 4;
    const int hl = rank / 3, role = rank - 3 * hl, tb = 3 * hl;
    const int head = (cl < 4 ? 5 * cl : 20 + 4 * (cl - 4)) + hl;
    const bool is_head = hl < nh;
    const int nown = 3 * nh;

    const int worker = cl < 4 ? cl : 4 + (cl - 4) * 4 + ((int)rank - 12);
    asm volatile("griddepcontrol.launch_dependents;");
    CAL(blockIdx.x, 0);
    if (tid == 0) {
        mbar_init(sb + MB_X, 1); mbar_init(sb + MB_X + 8, 1);
        for (int j = 0; j < 3; j++) mbar_init(sb + MB_M + 8 * j, 1);
        mbar_init(sb + MB_IN, 1); mbar_init(sb + MB_IN + 8, 1); mbar_init(sb + MB_IN + 16, 1); mbar_init(sb + MB_QC, 3);
        mbar_init(sb + MB_H1, 1); mbar_init(sb + MB_KV, 1); mbar_init(sb + MB_KV + 8, 1);
        mbar_init(sb + MB_FREE, 2); mbar_init(sb + MB_FREE + 8, 2); mbar_init(sb + MB_XD, 8); mbar_init(sb + MB_XD + 8, 8); mbar_init(sb + MB_WO, 96);
        asm volatile("fence.mbarrier_init.release.cluster;" ::: "memory");
        fence_async_smem();
        mbar_expect(sb + MB_X, 40960); mbar_expect(sb + MB_X + 8, 40960);
        if (!is_head) aux_init(sb);
    }
    __syncthreads();
    cluster_sync();
    const uint16_t tmask = (uint16_t)(7u << tb);
    if (tid == 0 && is_head) {
        for (int n = 0; n < 2; n++)
            for (int kb = role; kb < 10; kb += 3) tma3d_mc(sb + XT_OFF + n * 40960 + kb * 4096, &tmx, 0, 32 * n, kb, sb + MB_X + 8 * n, tmask);
    }

    if (warp < 8) {
        asm volatile("setmaxnreg.inc.sync.aligned.u32 224;");
        if (is_head) {
        const int lane_r = __shfl_sync(0xffffffffu, tid & 31, tid & 31);
        const int wg = warp >> 2, w = warp & 3;
        uint32_t A[40][4];
        {
            const bf16* W = role == 0 ? Wq : (role == 1 ? Wk : Wv);
            const bf16* wp = W + (size_t)(2 * t) * 4096 + head * 128 + 16 * warp + 2 * g;
#pragma unroll
            for (int ks = 0; ks < 40; ks++) {
                A[ks][0] = __ldg((const uint32_t*)(wp + (size_t)(16 * ks) * 4096));
                A[ks][1] = __ldg((const uint32_t*)(wp + (size_t)(16 * ks + 1) * 4096));
                A[ks][2] = __ldg((const uint32_t*)(wp + (size_t)(16 * ks + 8) * 4096));
                A[ks][3] = __ldg((const uint32_t*)(wp + (size_t)(16 * ks + 9) * 4096));
            }
#pragma unroll
            for (int ks = 0; ks < 40; ks++) {
                const uint32_t r0 = A[ks][0], r1 = A[ks][1], r2 = A[ks][2], r3 = A[ks][3];
                A[ks][0] = __byte_perm(r0, r1, 0x5410); A[ks][1] = __byte_perm(r0, r1, 0x7632);
                A[ks][2] = __byte_perm(r2, r3, 0x5410); A[ks][3] = __byte_perm(r2, r3, 0x7632);
            }
        }

        auto xproj = [&](int n) {
            const int st = n & 1;
            FRESH_LANE();
            const uint32_t a = sb + (role == 0 ? (st ? EX2_OFF : EX_OFF) : kv_off(role, role, n)) + (8 * (lane >> 4) + (lane & 7)) * KV_STRIDE + 32 * warp + ((lane >> 3) & 1) * 16;
            PIN(a);
            if (role == 0) { if (n >= 2) mbar_wait_u(sb + MB_QC, st); }
            else if (n >= 3) mbar_wait_u(sb + MB_FREE + 8 * ((n - 3) & 1), ((n - 3) >> 1) & 1);
            mbar_wait_u(sb + MB_X + 8 * st, (n >> 1) & 1);
            float acc[16];
            const uint32_t d0 = __shfl_sync(0xffffffffu, desc_sw128(sb + XT_OFF + st * 40960), 0);
            WG_FENCE();
#pragma unroll
            for (int ks = 0; ks < 40; ks++) wgmma_n32(acc, A[ks], d0 + (((ks >> 2) * 4096 + (ks & 3) * 32) >> 4), ks > 0);
            WG_COMMIT();
            WG_WAIT0();
            stsm4t(a, pack2(acc[0], acc[1]), pack2(acc[2], acc[3]), pack2(acc[4], acc[5]), pack2(acc[6], acc[7]));
            stsm4t(a + 16 * KV_STRIDE, pack2(acc[8], acc[9]), pack2(acc[10], acc[11]), pack2(acc[12], acc[13]), pack2(acc[14], acc[15]));
            fence_async_smem();
            __syncwarp();
            if (lane == 0) mbar_arrive(sb + MB_XD + 8 * st);
        };

        xproj(0);
        xproj(1);
#pragma unroll 1
        for (int s = 0; s < NSEG_; s++) {
            const int st = s & 1;
            if (warp == 4 && lane_r == 0) mbar_expect(sb + MB_H1, 6144);
            {
                float acc[4][4];
#pragma unroll
                for (int i = 0; i < 16; i++) ((float*)acc)[i] = 0.f;
                FRESH_LANE();
                const uint32_t mrd = sb + M_OFF + lane * 8;
                const uint32_t dl = sb + (role == 0 ? QF_OFF : (role == 1 ? KF_OFF : VF_OFF) + st * 2048) + warp * 256 + lane * 8;
                PIN(mrd); PIN(dl);
                mbar_wait_u(sb + MB_M, st);
                TS(0);
                uint2 b[40];
#pragma unroll
                for (int i = 0; i < 12; i++) b[i] = lds64(mrd + i * 256);
#pragma unroll
                for (int i = 0; i < 40; i++) {
                    if (i + 12 < 40) b[i + 12] = lds64(mrd + (i + 12) * 256);
                    mma16(acc[i & 3], A[i], b[i].x, b[i].y);
                }
                TS(1);
                uint32_t u0 = pack2((acc[0][0] + acc[1][0]) + (acc[2][0] + acc[3][0]), (acc[0][1] + acc[1][1]) + (acc[2][1] + acc[3][1]));
                uint32_t u1 = pack2((acc[0][2] + acc[1][2]) + (acc[2][2] + acc[3][2]), (acc[0][3] + acc[1][3]) + (acc[2][3] + acc[3][3]));
                if (role != 2) { u0 = movm(u0); u1 = movm(u1); }
#pragma unroll
                for (int r = 0; r < 3; r++) st_async8(mapa(dl, tb + r), u0, u1, mapa(sb + MB_H1, tb + r));
            }
            TS(2);
            if (s == NSEG_ - 1) break;
            if (s == 0) mbar_wait_u(sb + MB_WO, 0);
            uint32_t wa[8][4];
            const bool pair = wg || (w >= 2 && role != 2);
            const int tileA = wg ? 2 * w : (pair ? 6 + 2 * w : 8 + w);
            const uint32_t stg_hi = pair ? 32u : 64u * WO_STRIDE;
            int wA, rA, sA, wB, rB, sB;
            tile_owner(role * 14 + tileA, nown, wA, rA, sA); tile_owner(role * 14 + tileA + 1, nown, wB, rB, sB);
            uint32_t wb, inA, inB;
            {
                FRESH_LANE();
                wb = sb + WO_OFF + ((lane & 7) + (lane >> 4) * 8 + 64) * WO_STRIDE + ((lane >> 3) & 1) * 16 + tileA * 32;
                inA = mapa(sb + IN_OFF + (wA * 2 + sA) * 1280 + hl * 256 + lane * 8, rA); inB = mapa(sb + IN_OFF + (wB * 2 + sB) * 1280 + hl * 256 + lane * 8, rB);
                PIN(wb); PIN(inA); PIN(inB);
            }
            if (wg) {
                FRESH_LANE();
#pragma unroll
                for (int ks = 0; ks < 8; ks++) ldsm4t(wa[ks], wb - 64 * WO_STRIDE + (ks & 3) * 16 * WO_STRIDE + (ks >> 2) * stg_hi);
                if (w < 2) {
                    mbar_wait_u(sb + MB_H1, st);
                    if (lane == 0) {
                        if (w == 0) {
                            mbar_expect(sb + MB_M, 10240);
                        }
                        else {
                            for (int n = (s == 0 ? 2 : s + 3); n <= s + 3 && n < NSEG_; n++) {
                                mbar_expect(sb + MB_X + 8 * (n & 1), 40960);
                                for (int kb = role; kb < 10; kb += 3)
                                    tma3d_mc(sb + XT_OFF + (n & 1) * 40960 + kb * 4096, &tmx, 0, 32 * n, kb, sb + MB_X + 8 * (n & 1), tmask);
                            }
                        }
                    }
                    __syncwarp();
                }
            } else {
                FRESH_LANE();
                const uint32_t s_base = sb + M_OFF + role * 3584;
                const uint32_t r8 = (lane & 7) * KV_STRIDE;
                const int mt = w & 1, eh = w >> 1;
                mbar_wait_u(sb + MB_KV + 8 * st, (s >> 1) & 1);
                if (w == 3 && lane == 0) asm volatile("mbarrier.arrive.relaxed.cluster.shared::cluster.b64 _, [%0];" ::"r"(mapa(sb + MB_QC, tb)) : "memory");
                uint32_t vb[2][2][4];
                uint2 vm[2];
                {
                    const uint32_t ka = sb + kv_off(1, role, s) + eh * 128 + r8 + (16 * mt + ((lane >> 3) & 1) * 8) * KV_STRIDE + (lane >> 4) * 16;
                    const uint32_t fl = sb + lane * 8;
                    const uint32_t sw = s_base + eh * 1280 + mt * 64 + t * 320 + g * 4;
                    const uint32_t sm = s_base + 2560 + w * 256 + t * 64 + g * 4;
                    uint32_t a[4][4];
#pragma unroll
                    for (int k = 0; k < 4; k++) ldsm4(a[k], ka + k * 32);
                    const uint32_t va1 = sb + kv_off(2, role, s) + w * 64 + r8 + ((lane >> 3) & 1) * 8 * KV_STRIDE + (lane >> 4) * 16;
                    ldsm4t(vb[0][0], va1); ldsm4t(vb[0][1], va1 + 32);
                    ldsm4t(vb[1][0], va1 + 16 * KV_STRIDE); ldsm4t(vb[1][1], va1 + 16 * KV_STRIDE + 32);
                    PIN(fl); PIN(sw); PIN(sm);
                    mbar_wait_u(sb + MB_H1, st);
                    TS(3);
                    uint2 b[4], am[2], bm[2];
#pragma unroll
                    for (int k = 0; k < 4; k++) b[k] = lds64(fl + QF_OFF + (4 * eh + k) * 256);
#pragma unroll
                    for (int k = 0; k < 2; k++) { am[k] = lds64(fl + KF_OFF + st * 2048 + (2 * w + k) * 256); bm[k] = lds64(fl + QF_OFF + (2 * w + k) * 256); }
                    float c0[4] = {0, 0, 0, 0}, c1[4] = {0, 0, 0, 0}, c2[4] = {0, 0, 0, 0}, c3[4] = {0, 0, 0, 0};
                    mma16(c0, a[0], b[0].x, b[0].y); mma16(c1, a[1], b[1].x, b[1].y);
                    mma16r(c2, am[0].x, 0u, am[0].y, 0u, bm[0].x, bm[0].y);
                    mma16r(c3, am[1].x, 0u, am[1].y, 0u, bm[1].x, bm[1].y);
                    mma16(c0, a[2], b[2].x, b[2].y); mma16(c1, a[3], b[3].x, b[3].y);
                    sts32f(sm, c2[0] + c3[0]); sts32f(sm + 32, c2[1] + c3[1]);
                    sts32f(sw, c0[0] + c1[0]); sts32f(sw + 160, c0[1] + c1[1]);
                    sts32f(sw + 32, c0[2] + c1[2]); sts32f(sw + 160 + 32, c0[3] + c1[3]);
#pragma unroll
                    for (int k = 0; k < 2; k++) vm[k] = lds64(fl + VF_OFF + st * 2048 + (2 * w + k) * 256);
                }
                const uint32_t sr = s_base + g * 160 + t * 8;
                bar_sync(7, 128);
                TS(4);
                float sc[10];
                {
                    float2 m[4], p0[4], p1[4];
#pragma unroll
                    for (int j = 0; j < 4; j++) { p0[j] = lds64f(sr + j * 32); p1[j] = lds64f(sr + 1280 + j * 32); }
#pragma unroll
                    for (int j = 0; j < 4; j++) m[j] = lds64f(s_base + 2560 + j * 256 + lane * 8);
#pragma unroll
                    for (int j = 0; j < 4; j++) { sc[2 + 2 * j] = p0[j].x + p1[j].x; sc[3 + 2 * j] = p0[j].y + p1[j].y; }
                    sc[0] = (m[0].x + m[1].x) + (m[2].x + m[3].x); sc[1] = (m[0].y + m[1].y) + (m[2].y + m[3].y);
                }
                float mx = fmaxf(fmaxf(fmaxf(sc[2], sc[3]), fmaxf(sc[4], sc[5])), fmaxf(fmaxf(sc[6], sc[7]), fmaxf(sc[8], sc[9])));
                mx = fmaxf(mx, fmaxf(sc[0], sc[1]));
                mx = fmaxf(mx, __shfl_xor_sync(~0u, mx, 1)); mx = fmaxf(mx, __shfl_xor_sync(~0u, mx, 2));
                const float nm = -mx * (SCALE * LOG2E);
#pragma unroll
                for (int i = 0; i < 10; i++) sc[i] = ex2(fmaf(sc[i], SCALE * LOG2E, nm));
                uint32_t p[5];
#pragma unroll
                for (int j = 0; j < 5; j++) p[j] = pack2(sc[2 * j], sc[2 * j + 1]);
                float o[4][4];
#pragma unroll
                for (int i = 0; i < 16; i++) ((float*)o)[i] = 0.f;
#pragma unroll
                for (int n = 0; n < 4; n++) mma8(o[n], p[0], 0u, (n & 1) ? vm[n >> 1].y : vm[n >> 1].x);
#pragma unroll
                for (int n = 0; n < 4; n++) mma16r(o[n], p[1], 0u, p[2], 0u, vb[0][n >> 1][2 * (n & 1)], vb[0][n >> 1][2 * (n & 1) + 1]);
#pragma unroll
                for (int n = 0; n < 4; n++) mma16r(o[n], p[3], 0u, p[4], 0u, vb[1][n >> 1][2 * (n & 1)], vb[1][n >> 1][2 * (n & 1) + 1]);
                float sum = ((sc[0] + sc[1]) + (sc[2] + sc[3])) + ((sc[4] + sc[5]) + (sc[6] + sc[7])) + (sc[8] + sc[9]);
                sum += __shfl_xor_sync(~0u, sum, 1); sum += __shfl_xor_sync(~0u, sum, 2);
                const float inv = rcp(sum);
                sts128(sb + O_OFF + w * 512 + l16,
                       make_uint4(pack2(o[0][0] * inv, o[0][1] * inv), pack2(o[1][0] * inv, o[1][1] * inv),
                                  pack2(o[2][0] * inv, o[2][1] * inv), pack2(o[3][0] * inv, o[3][1] * inv)));
#pragma unroll
                for (int ks = 0; ks < 8; ks++) ldsm4t(wa[ks], wb - 64 * WO_STRIDE + (ks & 3) * 16 * WO_STRIDE + (ks >> 2) * stg_hi);
            }
            {
            FRESH_LANE();
            bar_sync(1, 256);
            TS(5);
            if (pair) {
                float d[4][4];
#pragma unroll
                for (int i = 0; i < 16; i++) ((float*)d)[i] = 0.f;
#pragma unroll
                for (int hf = 0; hf < 2; hf++) {
                    const uint4 o0 = lds128(sb + O_OFF + hf * 1024 + l16), o1 = lds128(sb + O_OFF + hf * 1024 + 512 + l16);
                    mma16(d[0], wa[0], o0.x, o0.y); mma16(d[2], wa[4], o0.x, o0.y);
                    mma16(d[1], wa[1], o0.z, o0.w); mma16(d[3], wa[5], o0.z, o0.w);
                    if (hf == 0) { ldsm4t(wa[0], wb); ldsm4t(wa[4], wb + 32); ldsm4t(wa[1], wb + 16 * WO_STRIDE); ldsm4t(wa[5], wb + 16 * WO_STRIDE + 32); }
                    mma16(d[0], wa[2], o1.x, o1.y); mma16(d[2], wa[6], o1.x, o1.y);
                    mma16(d[1], wa[3], o1.z, o1.w); mma16(d[3], wa[7], o1.z, o1.w);
                    if (hf == 0) {
                        ldsm4t(wa[2], wb + 32 * WO_STRIDE); ldsm4t(wa[6], wb + 32 * WO_STRIDE + 32);
                        ldsm4t(wa[3], wb + 48 * WO_STRIDE); ldsm4t(wa[7], wb + 48 * WO_STRIDE + 32);
                    }
                }
                st_async8(inA, pack2(d[0][0] + d[1][0], d[0][1] + d[1][1]), pack2(d[0][2] + d[1][2], d[0][3] + d[1][3]), mapa(sb + MB_IN + 8 * wA, rA));
                st_async8(inB, pack2(d[2][0] + d[3][0], d[2][1] + d[3][1]), pack2(d[2][2] + d[3][2], d[2][3] + d[3][3]), mapa(sb + MB_IN + 8 * wB, rB));
            } else {
                float d[2][4];
#pragma unroll
                for (int i = 0; i < 8; i++) ((float*)d)[i] = 0.f;
#pragma unroll
                for (int k = 0; k < 4; k++) {
                    const uint4 o0 = lds128(sb + O_OFF + k * 512 + l16);
                    mma16(d[0], wa[2 * k], o0.x, o0.y); mma16(d[1], wa[2 * k + 1], o0.z, o0.w);
                }
                st_async8(inA, pack2(d[0][0] + d[1][0], d[0][1] + d[1][1]), pack2(d[0][2] + d[1][2], d[0][3] + d[1][3]), mapa(sb + MB_IN + 8 * wA, rA));
            }
            }
            TS(6);
            TSV(14, threadIdx.x == 224, clk());
            if (s + 2 < NSEG_) xproj(s + 2);
            TS(7);
        }
        if (warp == 0) { mbar_wait_u(sb + MB_H1, 1); mbar_wait_u(sb + MB_KV + 8, 1); mbar_wait_u(sb + MB_FREE, 1); mbar_wait_u(sb + MB_FREE + 8, 1); if (role == 0) mbar_wait_u(sb + MB_QC, 0); }
        }
        else aux_compute(P, smem, sb, worker, warp);
    } else {
      asm volatile("setmaxnreg.dec.sync.aligned.u32 56;");
      if (warp < 11) {
        const int cw = warp - 8, ct = cw * 32 + lane;
        int idx = (int)rank - 5 * cw; if (idx < 0) idx += nown;
        const bool own = (int)rank < nown && idx < (cw == 2 ? 12 : 14);
        const int T = 14 * cw + idx;
        const bool own2 = own && idx + nown < (cw == 2 ? 12 : 14);
        if (own) st_rel8(&g_X[2][(T * 7 + cl) * 32 + lane], 0u, 0u);
        if (own2) st_rel8(&g_X[2][((T + nown) * 7 + cl) * 32 + lane], 0u, 0u);
        if (is_head) {
            uint2 mv[14];
#pragma unroll
            for (int j = 0; j < 14; j++) {
                const int p = min(ct + 96 * j, 1279), ks = p >> 5, l = p & 31;
                const uint32_t* mp = (const uint32_t*)(mem0 + (l >> 2) * DM_ + ks * 16 + 2 * (l & 3));
                mv[j] = make_uint2(__ldg(mp), __ldg(mp + 4));
            }
            const int nch = role == 2 ? 24 : 28;
            for (int r = cw; r < 128; r += 3) {
                if (lane < nch) cp_async16(sb + WO_OFF + r * WO_STRIDE + lane * 16, Wo + (size_t)(head * 128 + eperm(r)) * DM_ + role * 224 + lane * 8);
            }
            asm volatile("cp.async.mbarrier.arrive.noinc.shared.b64 [%0];" ::"r"(sb + MB_WO) : "memory");
#pragma unroll
            for (int j = 0; j < 14; j++) {
                const int p = min(ct + 96 * j, 1279);
                sts64(sb + M_OFF + p * 8, mv[j].x, mv[j].y);
            }
            bar_sync(6, 96);
            if (ct == 0) mbar_arrive(sb + MB_M);
        }
        __threadfence();
        const bool sender = is_head && cw == 2;
        auto send_x = [&](int n) {
            const int st = n & 1;
            mbar_wait_u(sb + MB_XD + 8 * st, (n >> 1) & 1);
            if (n >= 1) mbar_wait_u(sb + MB_H1, (n - 1) & 1);
            if (n >= 2) mbar_wait_u(sb + MB_FREE + 8 * st, ((n - 2) >> 1) & 1);
            const int a0 = (2 * n) % 3, a1 = (2 * n + 1) % 3;
            const uint32_t mbkv = sb + MB_KV + 8 * st, qs = sb + (st ? EX2_OFF : EX_OFF);
            if (lane == 0) {
                if (role == 0) {
                    if (a0 != 0) bulk_s2s(mapa(sb + QX_OFF + st * QX_BYTES, tb + a0), qs, QX_BYTES, mapa(mbkv, tb + a0));
                    if (a1 != 0) bulk_s2s(mapa(sb + QX_OFF + st * QX_BYTES, tb + a1), qs + QX_BYTES, QX_BYTES, mapa(mbkv, tb + a1));
                } else {
                    const uint32_t src = sb + kv_off(role, role, n), dst = sb + kv_off(role, 0, n);
                    bulk_s2s(mapa(dst, tb), src, XB_BYTES, mapa(mbkv, tb));
                    bulk_s2s(mapa(dst, tb + 3 - role), src, XB_BYTES, mapa(mbkv, tb + 3 - role));
                }
            }
            if (role == 0 && (a0 == 0 || a1 == 0)) {
                const uint32_t src = qs + (a0 == 0 ? 0 : QX_BYTES);
                for (int i = lane; i < QX_BYTES / 16; i += 32) sts128(sb + QX_OFF + st * QX_BYTES + i * 16, lds128(src + i * 16));
            }
            __syncwarp();
            if (lane == 0) mbar_expect(mbkv, (role == 0 ? 2 * XB_BYTES : XB_BYTES) + (role != 0 && (a0 == role || a1 == role) ? QX_BYTES : 0));
            __syncwarp();
        };
        if (sender) send_x(0);
        auto owner_loop = [&](auto ntc) {
            constexpr int NT = decltype(ntc)::value;
            const uint32_t mdst = sb + M_OFF + T * 256 + lane * 8;
            const uint32_t mbar = sb + MB_M;
            if (own && lane == 0) mbar_expect(sb + MB_IN + 8 * cw, NT * nh * 256);
#pragma unroll 1
            for (int s = 0; s < NSEG_ - 1; s++) {
                if (sender) send_x(s + 1);
                if (!own) continue;
                int lane_o = lane;
                asm volatile("" : "+r"(lane_o));
                uint2* xs = &g_X[s & 3][T * 7 * 32 + lane_o];
                uint2* xw = xs + cl * 32;
                const uint32_t ib = sb + IN_OFF + cw * 2560 + lane_o * 8;
                asm volatile("" ::"l"(xw), "r"(ib));
                mbar_wait_u(sb + MB_IN + 8 * cw, s & 1);
                TS(10);
                uint2 v[NT][7];
#pragma unroll
                for (int u = 0; u < NT; u++) {
                    uint2 q[5];
#pragma unroll
                    for (int h = 0; h < 4; h++) q[h] = lds64(ib + u * 1280 + h * 256);
                    q[4] = make_uint2(0, 0);
                    if (NT == 1 && nh == 5) q[4] = lds64(ib + 1024);
#define SUM5(f, c) ((f(q[0].c) + f(q[1].c)) + (f(q[2].c) + f(q[3].c)) + f(q[4].c))
                    const uint32_t o0 = nzw(pack2(SUM5(bflo, x), SUM5(bfhi, x))), o1 = nzw(pack2(SUM5(bflo, y), SUM5(bfhi, y)));
                    st_rel8(xw + u * (12 * 7 * 32), o0, o1);
#pragma unroll
                    for (int c = 0; c < 7; c++) v[u][c] = c == cl ? make_uint2(o0, o1) : make_uint2(0, 0);
                }
                const int tw = clk();
                TS(11);
                if (lane == 0) mbar_expect(sb + MB_IN + 8 * cw, NT * nh * 256);
                while (clk() - tw < DELAY_X) {}
                int guard = 0;
                {
                    while (true) {
                        uint32_t chk = 0xffffffffu;
#pragma unroll
                        for (int u = 0; u < NT; u++)
#pragma unroll
                            for (int c = 0; c < 7; c++) if (min(v[u][c].x, v[u][c].y) == 0) v[u][c] = ld_poll8(xs + u * (12 * 7 * 32) + c * 32);
#pragma unroll
                        for (int u = 0; u < NT; u++)
#pragma unroll
                            for (int c = 0; c < 7; c++) chk = min(chk, min(v[u][c].x, v[u][c].y));
                        if (!__any_sync(~0u, chk == 0)) break;
                        if (++guard > SPIN_LIMIT) { g_misc[2] = 2; break; }
                    }
                }
                TS(12);
#pragma unroll
                for (int u = 0; u < NT; u++) {
#define SUM7(f, c) (((f(v[u][0].c) + f(v[u][1].c)) + (f(v[u][2].c) + f(v[u][3].c))) + ((f(v[u][4].c) + f(v[u][5].c)) + f(v[u][6].c)))
                    const uint32_t b0 = movm(pack2(SUM7(bflo, x), SUM7(bfhi, x))), b1 = movm(pack2(SUM7(bflo, y), SUM7(bfhi, y)));
                    int d = idx;
#pragma unroll
                    for (int r = 0; r < (NT == 2 ? 12 : 15); r++) {
                        if (r < 12 || nh == 5) st_async8(mapa(mdst + u * (12 * 256), d), b0, b1, mapa(mbar, d));
                        d = d + 1 == nown ? 0 : d + 1;
                    }
                }
                TS(13);
                TSV(15, threadIdx.x == 256, guard);
                if (s > 0) {
#pragma unroll
                    for (int u = 0; u < NT; u++) st_rel8(&g_X[(s - 1) & 3][((T + 12 * u) * 7 + cl) * 32 + lane_o], 0u, 0u);
                    __threadfence();
                }
            }
        };
        if (own2) owner_loop(std::integral_constant<int, 2>());
        else if (own || sender) owner_loop(std::integral_constant<int, 1>());
      } else if (is_head) {
        unsigned* cnt = &g_oxcnt[cl];
        int pending = -1;
#pragma unroll 1
        for (int task = role; task < 2 * NSEG_; task += 3) {
            const int s = task >> 1, mt = task & 1;
            const int st = s & 1;
            mbar_wait_u(sb + MB_KV + 8 * st, (s >> 1) & 1);
            mbar_wait_u(sb + MB_H1, st);
            TS(8);
            int lane = threadIdx.x & 31;
            asm volatile("" : "+r"(lane));
            const int g = lane >> 2, t = lane & 3;
            float sc[5][4];
#pragma unroll
            for (int i = 0; i < 20; i++) ((float*)sc)[i] = 0.f;
            const uint32_t r8 = (lane & 7) * KV_STRIDE;
            {
                const uint32_t qa = sb + QX_OFF + st * QX_BYTES + ((lane >> 3) & 1) * 8 * KV_STRIDE + r8 + (lane >> 4) * 16;
                const uint32_t ka = sb + kv_off(1, role, s) + r8 + ((lane >> 3) & 1) * 16 + (lane >> 4) * 8 * KV_STRIDE;
                const uint32_t kf = sb + KF_OFF + st * 2048 + lane * 8;
                uint32_t a[2][4], b0[2][4], b1[2][4]; uint2 bm[2];
                ldsm4(a[0], qa); bm[0] = lds64(kf); ldsm4(b0[0], ka); ldsm4(b1[0], ka + 16 * KV_STRIDE);
#pragma unroll
                for (int ks = 0; ks < 8; ks++) {
                    const int c = ks & 1, n = c ^ 1;
                    if (ks < 7) {
                        ldsm4(a[n], qa + (ks + 1) * 32); bm[n] = lds64(kf + (ks + 1) * 256);
                        ldsm4(b0[n], ka + (ks + 1) * 32); ldsm4(b1[n], ka + 16 * KV_STRIDE + (ks + 1) * 32);
                    }
                    mma16(sc[0], a[c], bm[c].x, bm[c].y);
                    mma16(sc[1], a[c], b0[c][0], b0[c][1]); mma16(sc[2], a[c], b0[c][2], b0[c][3]);
                    if (mt) { mma16(sc[3], a[c], b1[c][0], b1[c][1]); mma16(sc[4], a[c], b1[c][2], b1[c][3]); }
                }
            }
            if (pending >= 0) { if (lane == 0) red_rel(cnt + pending * 8, 1); pending = -1; __syncwarp(); }
            uint32_t p[5][2];
#pragma unroll
            for (int h = 0; h < 2; h++) {
                const int lim = 8 + 16 * mt + g + 8 * h - 2 * t;
                float mx = -3.0e38f;
#pragma unroll
                for (int j = 0; j < 5; j++) {
                    uint32_t r1 = pack2(sc[j][2 * h], sc[j][2 * h + 1]);
                    r1 = pack2(bflo(r1) * SCALE, bfhi(r1) * SCALE);
                    const float v0 = (8 * j <= lim) ? bflo(r1) : -1.0e9f, v1 = (8 * j + 1 <= lim) ? bfhi(r1) : -1.0e9f;
                    sc[j][2 * h] = v0; sc[j][2 * h + 1] = v1; mx = fmaxf(mx, fmaxf(v0, v1));
                }
                mx = fmaxf(mx, __shfl_xor_sync(~0u, mx, 1)); mx = fmaxf(mx, __shfl_xor_sync(~0u, mx, 2));
                float sum = 0.f;
#pragma unroll
                for (int j = 0; j < 5; j++) {
#pragma unroll
                    for (int i = 0; i < 2; i++) { float e = ex2((sc[j][2 * h + i] - mx) * LOG2E); sc[j][2 * h + i] = e; sum += e; }
                }
                sum += __shfl_xor_sync(~0u, sum, 1); sum += __shfl_xor_sync(~0u, sum, 2);
                const float inv = rcp(sum);
#pragma unroll
                for (int j = 0; j < 5; j++) p[j][h] = pack2(sc[j][2 * h] * inv, sc[j][2 * h + 1] * inv);
            }
            uint32_t* og = (uint32_t*)(g_ox + (size_t)(s * NH_ + head) * 512) + (16 * mt + g) * 32 + t;
            const uint32_t va = sb + kv_off(2, role, s) + r8 + ((lane >> 3) & 1) * 8 * KV_STRIDE + (lane >> 4) * 16;
            const uint32_t vf = sb + VF_OFF + st * 2048 + lane * 8;
            {
                uint32_t b0[2][4], b1[2][4]; uint2 bm[2];
                bm[0] = lds64(vf); ldsm4t(b0[0], va); ldsm4t(b1[0], va + 16 * KV_STRIDE);
#pragma unroll
                for (int np = 0; np < 8; np++) {
                    const int c = np & 1, nx = c ^ 1;
                    if (np < 7) { bm[nx] = lds64(vf + (np + 1) * 256); ldsm4t(b0[nx], va + (np + 1) * 32); ldsm4t(b1[nx], va + 16 * KV_STRIDE + (np + 1) * 32); }
                    float o[2][4] = {{0, 0, 0, 0}, {0, 0, 0, 0}};
                    mma8(o[0], p[0][0], p[0][1], bm[c].x); mma8(o[1], p[0][0], p[0][1], bm[c].y);
                    mma16r(o[0], p[1][0], p[1][1], p[2][0], p[2][1], b0[c][0], b0[c][1]);
                    mma16r(o[1], p[1][0], p[1][1], p[2][0], p[2][1], b0[c][2], b0[c][3]);
                    if (mt) {
                        mma16r(o[0], p[3][0], p[3][1], p[4][0], p[4][1], b1[c][0], b1[c][1]);
                        mma16r(o[1], p[3][0], p[3][1], p[4][0], p[4][1], b1[c][2], b1[c][3]);
                    }
#pragma unroll
                    for (int n = 0; n < 2; n++) {
                        const int ch = (2 * np + n) & 7;
                        int gx = g; asm volatile("" : "+r"(gx));
                        uint32_t* o2 = og + (np >> 2) * 1024 + ((ch ^ gx) << 2);
                        o2[0] = pack2(o[n][0], o[n][1]);
                        o2[256] = pack2(o[n][2], o[n][3]);
                    }
                }
            }
            __syncwarp();
            if (lane < 3) asm volatile("mbarrier.arrive.relaxed.cluster.shared::cluster.b64 _, [%0];" ::"r"(mapa(sb + MB_FREE + 8 * st, tb + lane)) : "memory");
            if (mt == 0 && task + 3 < 2 * NSEG_) pending = s;
            else if (lane == 0) red_rel(cnt + s * 8, 1);
            __syncwarp();
            TS(9);
        }
      }
      else if (lane == 0) aux_control(sb, worker);
    }
    __syncthreads();
    CAL(blockIdx.x, 1);
    cluster_sync();
}

__device__ bf16 f_mem[2][8 * DM_];
__device__ bf16 f_qkv[3][40 * 4096];
__device__ bf16 f_o[40 * 4096];
__global__ void fb_conv(const AuxArgs P) {
    __shared__ float u[S_], kk[S_];
    const int c = blockIdx.x;
    for (int t = threadIdx.x; t < S_; t += 256) {
        float a = 0.f;
        for (int tt = 0; tt < 4; tt++) { const int r = t + tt - 3; const float kv = r >= 0 ? __bfloat162float(P.Bk[(size_t)r * DM_ + c]) : 0.f; a = rbf(a + rbf(kv * __bfloat162float(P.shk[c * 4 + 3 - tt]))); }
        u[t] = rbf(a * __bfloat162float(P.Bv[(size_t)t * DM_ + c])); kk[t] = __bfloat162float(P.ssmk[(size_t)c * S_ + t]);
    }
    __syncthreads();
    const float D = __bfloat162float(P.ssmD[c]);
    for (int t = threadIdx.x; t < S_; t += 256) {
        float y = 0.f;
        for (int j = 0; j <= t; j++) y = fmaf(u[j], kk[t - j], y);
        g_b[(size_t)t * DM_ + c] = __float2bfloat16_rn(__bfloat162float(P.x[(size_t)t * DM_ + c]) * rbf(rbf(y) + rbf(u[t] * D)));
    }
}
__global__ void fb_proj(const bf16* x, const bf16* mem, const bf16* Wq, const bf16* Wk, const bf16* Wv, int s) {
    __shared__ bf16 h[40][DM_ / 2];
    const bf16* W = blockIdx.y == 0 ? Wq : (blockIdx.y == 1 ? Wk : Wv);
    const int col = blockIdx.x * 128 + threadIdx.x;
    float acc[40];
    for (int r = 0; r < 40; r++) acc[r] = 0.f;
    for (int half = 0; half < 2; half++) {
        __syncthreads();
        for (int i = threadIdx.x; i < 40 * 320; i += 128) { const int r = i / 320, d = i % 320 + half * 320; h[r][i % 320] = r < 8 ? mem[r * DM_ + d] : x[(size_t)(s * 32 + r - 8) * DM_ + d]; }
        __syncthreads();
        for (int d = 0; d < 320; d++) {
            const float wv = __bfloat162float(W[(size_t)(d + half * 320) * 4096 + col]);
#pragma unroll
            for (int r = 0; r < 40; r++) acc[r] = fmaf(__bfloat162float(h[r][d]), wv, acc[r]);
        }
    }
    for (int r = 0; r < 40; r++) f_qkv[blockIdx.y][r * 4096 + col] = __float2bfloat16_rn(acc[r]);
}
__global__ void fb_attn() {
    __shared__ float p[40][41];
    const int hb = blockIdx.x * 128;
    for (int i = threadIdx.x; i < 1600; i += 128) {
        const int q = i / 40, k = i % 40; float a = 0.f;
        for (int e = 0; e < 128; e++) a = fmaf(__bfloat162float(f_qkv[0][q * 4096 + hb + e]), __bfloat162float(f_qkv[1][k * 4096 + hb + e]), a);
        p[q][k] = (q < 8 || q >= k) ? rbf(rbf(a) * 0.08838834764831845f) : -1.0e9f;
    }
    __syncthreads();
    if (threadIdx.x < 40) {
        float* r = p[threadIdx.x]; float mx = r[0], sum = 0.f;
        for (int k = 1; k < 40; k++) mx = fmaxf(mx, r[k]);
        for (int k = 0; k < 40; k++) { r[k] = expf(r[k] - mx); sum += r[k]; }
        for (int k = 0; k < 40; k++) r[k] = rbf(r[k] / sum);
    }
    __syncthreads();
    for (int q = 0; q < 40; q++) {
        float a = 0.f;
        for (int k = 0; k < 40; k++) a = fmaf(p[q][k], __bfloat162float(f_qkv[2][k * 4096 + hb + threadIdx.x]), a);
        f_o[q * 4096 + hb + threadIdx.x] = __float2bfloat16_rn(a);
    }
}
__global__ void fb_out(const AuxArgs P, bf16* memn, int s) {
    __shared__ float o[4096]; __shared__ float red[128];
    const int r = blockIdx.x, c = blockIdx.y * 128 + threadIdx.x;
    for (int i = threadIdx.x; i < 4096; i += 128) o[i] = __bfloat162float(f_o[r * 4096 + i]);
    const int row = s * 32 + r - 8;
    float ga = 0.f;
    if (r >= 8) for (int d = threadIdx.x; d < DM_; d += 128) ga += rbf(__bfloat162float(P.x[(size_t)row * DM_ + d]) * __bfloat162float(P.gatew[d]));
    red[threadIdx.x] = ga;
    __syncthreads();
    float a = 0.f;
    for (int k = 0; k < 4096; k++) a = fmaf(o[k], __bfloat162float(P.Wo[(size_t)k * DM_ + c]), a);
    if (r < 8) { memn[r * DM_ + c] = __float2bfloat16_rn(a); return; }
    ga = 0.f; for (int i = 0; i < 128; i++) ga += red[i];
    const float gt = rbf(1.f / (1.f + expf(-rbf(ga)))), og = rbf(1.f - gt);
    P.out[(size_t)row * DM_ + c] = __float2bfloat16_rn(rbf(gt * rbf(a)) + rbf(og * __bfloat162float(g_b[(size_t)row * DM_ + c])));
}

typedef CUresult (*EncodeFn)(CUtensorMap*, CUtensorMapDataType, cuuint32_t, void*, const cuuint64_t*, const cuuint64_t*,
                             const cuuint32_t*, const cuuint32_t*, CUtensorMapInterleave, CUtensorMapSwizzle,
                             CUtensorMapL2promotion, CUtensorMapFloatOOBfill);

extern "C" void kernel_launch(void* const* d_in, const int* in_sizes, int n_in, void* d_out, int out_size) {
    const bf16* x = (const bf16*)d_in[0];
    const bf16* mem0 = (const bf16*)d_in[1];
    const bf16* Wq = (const bf16*)d_in[2];
    const bf16* Wk = (const bf16*)d_in[3];
    const bf16* Wv = (const bf16*)d_in[4];
    const bf16* Wo = (const bf16*)d_in[5];
    const bf16* Bk = (const bf16*)d_in[8];
    const bf16* Bv = (const bf16*)d_in[9];
    const bf16* shk = (const bf16*)d_in[10];
    const bf16* ssmk = (const bf16*)d_in[11];
    const bf16* ssmD = (const bf16*)d_in[12];
    const bf16* gatew = (const bf16*)d_in[13];

    static EncodeFn enc = nullptr;
    static int fast = -1;
    if (fast < 0) {
        void* fn = nullptr; cudaDriverEntryPointQueryResult qr;
        cudaGetDriverEntryPoint("cuTensorMapEncodeTiled", &fn, cudaEnableDefault, &qr);
        enc = (EncodeFn)fn;
        cudaFuncSetAttribute(rec_kernel, cudaFuncAttributeMaxDynamicSharedMemorySize, A_SMEM + 1024);
        cudaFuncSetAttribute(rec_kernel, cudaFuncAttributeNonPortableClusterSizeAllowed, 1);
        cudaFuncSetAttribute(aux_kernel, cudaFuncAttributeMaxDynamicSharedMemorySize, B_SMEM);
        cudaLaunchConfig_t qc = {};
        qc.gridDim = dim3(A_CTAS); qc.blockDim = dim3(A_THREADS); qc.dynamicSmemBytes = A_SMEM + 1024;
        cudaLaunchAttribute qa[1];
        qa[0].id = cudaLaunchAttributeClusterDimension; qa[0].val.clusterDim.x = 16; qa[0].val.clusterDim.y = 1; qa[0].val.clusterDim.z = 1;
        qc.attrs = qa; qc.numAttrs = 1;
        int ncl = 0, nsm = 0, dev = 0;
        cudaGetDevice(&dev);
        cudaDeviceGetAttribute(&nsm, cudaDevAttrMultiProcessorCount, dev);
        if (cudaOccupancyMaxActiveClusters(&ncl, rec_kernel, &qc) != cudaSuccess) { ncl = 0; cudaGetLastError(); }
        fast = (enc != nullptr && ncl >= 7 && nsm >= A_CTAS + NB_CTAS - N_SPARE) ? 1 : 0;
    }
    if (!fast) {
        cudaStream_t fs = cudaStreamPerThread;
        AuxArgs FP = {x, Wo, Bk, Bv, shk, ssmk, ssmD, gatew, (bf16*)d_out};
        bf16* fm; cudaGetSymbolAddress((void**)&fm, f_mem);
        fb_conv<<<DM_, 256, 0, fs>>>(FP);
        for (int s = 0; s < NSEG_; s++) {
            fb_proj<<<dim3(32, 3), 128, 0, fs>>>(x, s == 0 ? mem0 : fm + (s & 1) * 8 * DM_, Wq, Wk, Wv, s);
            fb_attn<<<32, 128, 0, fs>>>();
            fb_out<<<dim3(40, 5), 128, 0, fs>>>(FP, fm + ((s + 1) & 1) * 8 * DM_, s);
        }
        return;
    }
    CUtensorMap tmx;
    {
        cuuint64_t dims[3] = {64, (cuuint64_t)S_, 10};
        cuuint64_t strides[2] = {DM_ * 2, 128};
        cuuint32_t box[3] = {64, 32, 1}, es[3] = {1, 1, 1};
        enc(&tmx, CU_TENSOR_MAP_DATA_TYPE_BFLOAT16, 3, (void*)x, dims, strides, box, es, CU_TENSOR_MAP_INTERLEAVE_NONE,
            CU_TENSOR_MAP_SWIZZLE_128B, CU_TENSOR_MAP_L2_PROMOTION_L2_256B, CU_TENSOR_MAP_FLOAT_OOB_FILL_NONE);
    }
    cudaStream_t st = cudaStreamPerThread;
    AuxArgs P = {x, Wo, Bk, Bv, shk, ssmk, ssmD, gatew, (bf16*)d_out};
    {
        cudaLaunchConfig_t ca = {};
        ca.gridDim = dim3(A_CTAS); ca.blockDim = dim3(A_THREADS); ca.dynamicSmemBytes = A_SMEM + 1024; ca.stream = st;
        cudaLaunchAttribute aa[1];
        aa[0].id = cudaLaunchAttributeClusterDimension; aa[0].val.clusterDim.x = 16; aa[0].val.clusterDim.y = 1; aa[0].val.clusterDim.z = 1;
        ca.attrs = aa; ca.numAttrs = 1;
        cudaLaunchKernelEx(&ca, rec_kernel, tmx, mem0, Wq, Wk, Wv, Wo, P);
    }
    cudaLaunchConfig_t cfg = {};
    cfg.gridDim = dim3(NB_CTAS - N_SPARE);
    cfg.blockDim = dim3(B_THREADS); cfg.dynamicSmemBytes = B_SMEM; cfg.stream = st;
    cudaLaunchAttribute at[1];
    at[0].id = cudaLaunchAttributeProgrammaticStreamSerialization; at[0].val.programmaticStreamSerializationAllowed = 1;
    cfg.attrs = at; cfg.numAttrs = 1;
    cudaLaunchKernelEx(&cfg, aux_kernel, P);
}
```

```cpp
#include <cuda_runtime.h>
#include <cuda_bf16.h>
#include <cuda.h>
#include <stdint.h>
#include <type_traits>

typedef __nv_bfloat16 bf16;

constexpr int S_ = 2048, DM_ = 640, NH_ = 32, NSEG_ = 64;
constexpr int NKG_ = 7, NCR_ = 5, NB_CTAS = NKG_ * NCR_;

#define DELAY_X 200
#define LOOKW 20
#define SPIN_LIMIT (1 << 13)
#define SPIN_FAIL(guard, code) (((++guard) & 1023) == 0 && (guard >= SPIN_LIMIT || *(volatile unsigned*)&g_misc[2] != 0) && ((g_misc[2] = (code)), true))

__device__ uint2 g_X[4][40 * 7 * 32];
__device__ uint4 g_ox[(size_t)NSEG_ * NH_ * 512];
__device__ float g_part[(size_t)NKG_ * S_ * DM_];
__device__ bf16 g_b[(size_t)S_ * DM_];
__device__ float g_gate[S_];
__device__ unsigned g_oxcnt[NSEG_ * 8];
__device__ unsigned g_pcnt[NSEG_ * 8];
__device__ unsigned g_misc[4];
#define CAL(b, i) do {} while (0)

__device__ __forceinline__ uint32_t smem_u32(const void* p) { return (uint32_t)__cvta_generic_to_shared(p); }
__device__ __forceinline__ void mbar_init(uint32_t mb, int cnt) { asm volatile("mbarrier.init.shared.b64 [%0], %1;" ::"r"(mb), "r"(cnt)); }
__device__ __forceinline__ void mbar_expect(uint32_t mb, int bytes) { asm volatile("mbarrier.arrive.expect_tx.shared.b64 _, [%0], %1;" ::"r"(mb), "r"(bytes) : "memory"); }
__device__ __forceinline__ void mbar_arrive(uint32_t mb) { asm volatile("mbarrier.arrive.shared.b64 _, [%0];" ::"r"(mb) : "memory"); }
__device__ __forceinline__ bool mbar_try(uint32_t mb, int parity) {
    uint32_t ok;
    asm volatile("{ .reg .pred p; mbarrier.try_wait.parity.shared.b64 p, [%1], %2; selp.u32 %0, 1, 0, p; }" : "=r"(ok) : "r"(mb), "r"(parity) : "memory");
    return ok;
}
__device__ __forceinline__ void mbar_wait(uint32_t mb, int parity) {
    int guard = 0;
    while (!mbar_try(mb, parity)) { if (SPIN_FAIL(guard, 1)) break; }
}
__device__ __forceinline__ void mbar_wait_u(uint32_t mb, int parity) {
    asm volatile("{ .reg .pred p; .reg .u32 c; mov.u32 c, 0;\n"
                 "WL%=: mbarrier.try_wait.parity.shared.b64 p, [%0], %1;\n"
                 "@p bra.uni WD%=;\n"
                 "add.u32 c, c, 1; setp.lt.u32 p, c, 16384;\n"
                 "@p bra.uni WL%=;\n"
                 "WD%=: }" ::"r"(mb), "r"(parity) : "memory");
}
__device__ __forceinline__ uint32_t movm(uint32_t a) { uint32_t d; asm volatile("movmatrix.sync.aligned.m8n8.trans.b16 %0, %1;" : "=r"(d) : "r"(a)); return d; }
__device__ __forceinline__ float ex2(float x) { float y; asm("ex2.approx.ftz.f32 %0, %1;" : "=f"(y) : "f"(x)); return y; }
__device__ __forceinline__ float rcp(float x) { float y; asm("rcp.approx.ftz.f32 %0, %1;" : "=f"(y) : "f"(x)); return y; }
__device__ __forceinline__ uint32_t mapa(uint32_t a, uint32_t r) { uint32_t o; asm volatile("mapa.shared::cluster.u32 %0, %1, %2;" : "=r"(o) : "r"(a), "r"(r)); return o; }
__device__ __forceinline__ uint4 ld_poll16(const void* p) { uint4 v; asm volatile("ld.relaxed.gpu.global.v4.u32 {%0,%1,%2,%3}, [%4];" : "=r"(v.x), "=r"(v.y), "=r"(v.z), "=r"(v.w) : "l"(p) : "memory"); return v; }
__device__ __forceinline__ void st_rel16(void* p, uint4 v) { asm volatile("st.relaxed.gpu.global.v4.u32 [%0], {%1,%2,%3,%4};" ::"l"(p), "r"(v.x), "r"(v.y), "r"(v.z), "r"(v.w) : "memory"); }
__device__ __forceinline__ void st_rel4(void* p, uint32_t v) { asm volatile("st.relaxed.gpu.global.u32 [%0], %1;" ::"l"(p), "r"(v) : "memory"); }
__device__ __forceinline__ unsigned ld_acq(const unsigned* p) { unsigned v; asm volatile("ld.acquire.gpu.global.u32 %0, [%1];" : "=r"(v) : "l"(p) : "memory"); return v; }
__device__ __forceinline__ void red_rel(unsigned* p, unsigned v) { asm volatile("red.release.gpu.global.add.u32 [%0], %1;" ::"l"(p), "r"(v) : "memory"); }
__device__ __forceinline__ void bar_sync(int id, int n) { asm volatile("bar.sync %0, %1;" ::"r"(id), "r"(n) : "memory"); }
__device__ __forceinline__ void st_async8(uint32_t dst, uint32_t a, uint32_t b, uint32_t mb) {
    asm volatile("st.async.weak.shared::cluster.mbarrier::complete_tx::bytes.v2.b32 [%0], {%1,%2}, [%3];" ::"r"(dst), "r"(a), "r"(b), "r"(mb) : "memory");
}
__device__ __forceinline__ void st_async16(uint32_t dst, uint32_t a, uint32_t b, uint32_t c, uint32_t d, uint32_t mb) {
    asm volatile("st.async.weak.shared::cluster.mbarrier::complete_tx::bytes.v4.b32 [%0], {%1,%2,%3,%4}, [%5];" ::"r"(dst), "r"(a), "r"(b), "r"(c), "r"(d), "r"(mb) : "memory");
}
__device__ __forceinline__ uint2 lds64(uint32_t a) { uint2 v; asm volatile("ld.shared.v2.u32 {%0,%1}, [%2];" : "=r"(v.x), "=r"(v.y) : "r"(a) : "memory"); return v; }
__device__ __forceinline__ uint2 ld_poll8(const void* p) { uint2 v; asm volatile("ld.relaxed.gpu.global.v2.u32 {%0,%1}, [%2];" : "=r"(v.x), "=r"(v.y) : "l"(p) : "memory"); return v; }
__device__ __forceinline__ void bulk_s2s(uint32_t dst, uint32_t src, uint32_t bytes, uint32_t mb) {
    asm volatile("cp.async.bulk.shared::cluster.shared::cta.mbarrier::complete_tx::bytes [%0], [%1], %2, [%3];" ::"r"(dst), "r"(src), "r"(bytes), "r"(mb) : "memory");
}
__device__ __forceinline__ void bulk_g2s(uint32_t dst, const void* src, uint32_t bytes, uint32_t mb) {
    asm volatile("cp.async.bulk.shared::cluster.global.mbarrier::complete_tx::bytes [%0], [%1], %2, [%3];" ::"r"(dst), "l"(src), "r"(bytes), "r"(mb) : "memory");
}
__device__ __forceinline__ void tma3d(uint32_t dst, const CUtensorMap* tm, int c0, int c1, int c2, uint32_t mb) {
    asm volatile("cp.async.bulk.tensor.3d.shared::cluster.global.mbarrier::complete_tx::bytes [%0], [%1, {%3, %4, %5}], [%2];"
                 ::"r"(dst), "l"((uint64_t)tm), "r"(mb), "r"(c0), "r"(c1), "r"(c2) : "memory");
}
__device__ __forceinline__ void tma3d_mc(uint32_t dst, const CUtensorMap* tm, int c0, int c1, int c2, uint32_t mb, uint16_t mask) {
    asm volatile("cp.async.bulk.tensor.3d.shared::cluster.global.mbarrier::complete_tx::bytes.multicast::cluster [%0], [%1, {%3, %4, %5}], [%2], %6;"
                 ::"r"(dst), "l"((uint64_t)tm), "r"(mb), "r"(c0), "r"(c1), "r"(c2), "h"(mask) : "memory");
}
__device__ __forceinline__ void st_rel8(void* p, uint32_t a, uint32_t b) { asm volatile("st.relaxed.gpu.global.v2.u32 [%0], {%1,%2};" ::"l"(p), "r"(a), "r"(b) : "memory"); }
__device__ __forceinline__ void fence_async_smem() { asm volatile("fence.proxy.async.shared::cta;" ::: "memory"); }
__device__ __forceinline__ void fence_async_all() { asm volatile("fence.proxy.async;" ::: "memory"); }
__device__ __forceinline__ void cp_async16(uint32_t dst, const void* src) { asm volatile("cp.async.cg.shared.global [%0], [%1], 16;" ::"r"(dst), "l"(src) : "memory"); }
__device__ __forceinline__ void cluster_sync() { asm volatile("barrier.cluster.arrive.aligned; barrier.cluster.wait.aligned;" ::: "memory"); }
__device__ __forceinline__ int clk() { int c; asm volatile("mov.u32 %0, %%clock;" : "=r"(c)); return c; }

__device__ __forceinline__ void ldsm4(uint32_t* r, uint32_t a) { asm volatile("ldmatrix.sync.aligned.m8n8.x4.shared.b16 {%0,%1,%2,%3}, [%4];" : "=r"(r[0]), "=r"(r[1]), "=r"(r[2]), "=r"(r[3]) : "r"(a) : "memory"); }
__device__ __forceinline__ void ldsm2(uint32_t* r, uint32_t a) { asm volatile("ldmatrix.sync.aligned.m8n8.x2.shared.b16 {%0,%1}, [%2];" : "=r"(r[0]), "=r"(r[1]) : "r"(a) : "memory"); }
__device__ __forceinline__ void ldsm4t(uint32_t* r, uint32_t a) { asm volatile("ldmatrix.sync.aligned.m8n8.x4.trans.shared.b16 {%0,%1,%2,%3}, [%4];" : "=r"(r[0]), "=r"(r[1]), "=r"(r[2]), "=r"(r[3]) : "r"(a) : "memory"); }
__device__ __forceinline__ void ldsm2t(uint32_t* r, uint32_t a) { asm volatile("ldmatrix.sync.aligned.m8n8.x2.trans.shared.b16 {%0,%1}, [%2];" : "=r"(r[0]), "=r"(r[1]) : "r"(a) : "memory"); }
__device__ __forceinline__ void stsm4t(uint32_t a, uint32_t r0, uint32_t r1, uint32_t r2, uint32_t r3) {
    asm volatile("stmatrix.sync.aligned.m8n8.x4.trans.shared.b16 [%0], {%1,%2,%3,%4};" ::"r"(a), "r"(r0), "r"(r1), "r"(r2), "r"(r3) : "memory");
}
__device__ __forceinline__ uint4 lds128(uint32_t a) { uint4 v; asm volatile("ld.shared.v4.u32 {%0,%1,%2,%3}, [%4];" : "=r"(v.x), "=r"(v.y), "=r"(v.z), "=r"(v.w) : "r"(a) : "memory"); return v; }
__device__ __forceinline__ float2 lds64f(uint32_t a) { float2 v; asm volatile("ld.shared.v2.f32 {%0,%1}, [%2];" : "=f"(v.x), "=f"(v.y) : "r"(a) : "memory"); return v; }
__device__ __forceinline__ float lds32f(uint32_t a) { float v; asm volatile("ld.shared.f32 %0, [%1];" : "=f"(v) : "r"(a) : "memory"); return v; }
__device__ __forceinline__ uint32_t lds32(uint32_t a) { uint32_t v; asm volatile("ld.shared.u32 %0, [%1];" : "=r"(v) : "r"(a) : "memory"); return v; }
__device__ __forceinline__ void sts128(uint32_t a, uint4 v) { asm volatile("st.shared.v4.u32 [%0], {%1,%2,%3,%4};" ::"r"(a), "r"(v.x), "r"(v.y), "r"(v.z), "r"(v.w) : "memory"); }
__device__ __forceinline__ void sts128f(uint32_t a, float x, float y, float z, float w) { asm volatile("st.shared.v4.f32 [%0], {%1,%2,%3,%4};" ::"r"(a), "f"(x), "f"(y), "f"(z), "f"(w) : "memory"); }
__device__ __forceinline__ void sts64f(uint32_t a, float x, float y) { asm volatile("st.shared.v2.f32 [%0], {%1,%2};" ::"r"(a), "f"(x), "f"(y) : "memory"); }
__device__ __forceinline__ void sts64(uint32_t a, uint32_t x, uint32_t y) { asm volatile("st.shared.v2.u32 [%0], {%1,%2};" ::"r"(a), "r"(x), "r"(y) : "memory"); }
__device__ __forceinline__ void sts32f(uint32_t a, float x) { asm volatile("st.shared.f32 [%0], %1;" ::"r"(a), "f"(x) : "memory"); }

__device__ __forceinline__ void mma16(float* d, const uint32_t* a, uint32_t b0, uint32_t b1) {
    asm volatile("mma.sync.aligned.m16n8k16.row.col.f32.bf16.bf16.f32 {%0,%1,%2,%3}, {%4,%5,%6,%7}, {%8,%9}, {%0,%1,%2,%3};"
                 : "+f"(d[0]), "+f"(d[1]), "+f"(d[2]), "+f"(d[3]) : "r"(a[0]), "r"(a[1]), "r"(a[2]), "r"(a[3]), "r"(b0), "r"(b1));
}
__device__ __forceinline__ void mma16r(float* d, uint32_t a0, uint32_t a1, uint32_t a2, uint32_t a3, uint32_t b0, uint32_t b1) {
    asm volatile("mma.sync.aligned.m16n8k16.row.col.f32.bf16.bf16.f32 {%0,%1,%2,%3}, {%4,%5,%6,%7}, {%8,%9}, {%0,%1,%2,%3};"
                 : "+f"(d[0]), "+f"(d[1]), "+f"(d[2]), "+f"(d[3]) : "r"(a0), "r"(a1), "r"(a2), "r"(a3), "r"(b0), "r"(b1));
}
__device__ __forceinline__ void mma8(float* d, uint32_t a0, uint32_t a1, uint32_t b0) {
    asm volatile("mma.sync.aligned.m16n8k8.row.col.f32.bf16.bf16.f32 {%0,%1,%2,%3}, {%4,%5}, {%6}, {%0,%1,%2,%3};"
                 : "+f"(d[0]), "+f"(d[1]), "+f"(d[2]), "+f"(d[3]) : "r"(a0), "r"(a1), "r"(b0));
}
__device__ __forceinline__ void wgmma_n32(float* d, const uint32_t* a, uint32_t desc_lo, int sc) {
    asm volatile("{ .reg .pred p; .reg .b64 dd; setp.ne.b32 p, %21, 0; mov.b64 dd, {%20, 0x40000040};\n"
                 "wgmma.mma_async.sync.aligned.m64n32k16.f32.bf16.bf16 {%0,%1,%2,%3,%4,%5,%6,%7,%8,%9,%10,%11,%12,%13,%14,%15}, {%16,%17,%18,%19}, dd, p, 1, 1, 0; }\n"
                 : "+f"(d[0]), "+f"(d[1]), "+f"(d[2]), "+f"(d[3]), "+f"(d[4]), "+f"(d[5]), "+f"(d[6]), "+f"(d[7]),
                   "+f"(d[8]), "+f"(d[9]), "+f"(d[10]), "+f"(d[11]), "+f"(d[12]), "+f"(d[13]), "+f"(d[14]), "+f"(d[15])
                 : "r"(a[0]), "r"(a[1]), "r"(a[2]), "r"(a[3]), "r"(desc_lo), "r"(sc));
}
#define WG_FENCE() asm volatile("wgmma.fence.sync.aligned;" ::: "memory")
#define WG_COMMIT() asm volatile("wgmma.commit_group.sync.aligned;" ::: "memory")
#define WG_WAIT0() asm volatile("wgmma.wait_group.sync.aligned 0;" ::: "memory")
__device__ __forceinline__ uint32_t desc_sw128(uint32_t saddr) { return ((saddr & 0x3FFFF) >> 4) | (1u << 16); }
__device__ __forceinline__ uint32_t pack2(float lo, float hi) { __nv_bfloat162 h = __floats2bfloat162_rn(lo, hi); return *(uint32_t*)&h; }
__device__ __forceinline__ float bflo(uint32_t u) { return __uint_as_float(u << 16); }
__device__ __forceinline__ float bfhi(uint32_t u) { return __uint_as_float(u & 0xffff0000u); }
__device__ __forceinline__ float rbf(float x) { return __uint_as_float(pack2(0.f, x)); }
__device__ __forceinline__ uint32_t nzw(uint32_t u) { return u == 0 ? 0x80008000u : u; }
__device__ __forceinline__ uint32_t min4(uint4 v) { return min(min(v.x, v.y), min(v.z, v.w)); }
__device__ __forceinline__ void mbar_arrive_if(uint32_t mb, uint32_t c) {
    asm volatile("{ .reg .pred p; setp.ne.u32 p, %1, 0; @p mbarrier.arrive.shared.b64 _, [%0]; }" ::"r"(mb), "r"(c) : "memory");
}
__device__ __forceinline__ int eperm(int p) { return (p & ~15) + 2 * (p & 7) + ((p >> 3) & 1); }

constexpr int U_STRIDE = 136 * 48;
constexpr int KR_STRIDE = 2080 * 2 * 2;
constexpr int B_U_OFF = 0, B_KR_OFF = 8 * U_STRIDE, B_CONV_END = B_KR_OFF + 8 * KR_STRIDE;
constexpr int B_OX_STAGES = 3, B_OX_BYTES = 40960;
constexpr int B_BAR_OFF = B_OX_STAGES * B_OX_BYTES;
constexpr int B_SMEM = B_BAR_OFF + 128;

constexpr int B_THREADS = 384;
constexpr int B_LAG = 2;

struct AuxArgs { const bf16 *x, *Wo, *Bk, *Bv, *shk, *ssmk, *ssmD, *gatew; bf16* out; };
constexpr int MBB_FULL = B_BAR_OFF, MBB_EMPTY = B_BAR_OFF + 24, MBB_ST = B_BAR_OFF + 48, MBB_GO = B_BAR_OFF + 80, MBB_FLAG = B_BAR_OFF + 96;

__device__ __forceinline__ void aux_init(uint32_t sb) {
    for (int i = 0; i < B_OX_STAGES; i++) { mbar_init(sb + MBB_FULL + 8 * i, 1); mbar_init(sb + MBB_EMPTY + 8 * i, 8); }
    for (int i = 0; i < 4; i++) mbar_init(sb + MBB_ST + 8 * i, 8);
    mbar_init(sb + MBB_GO, 8);
    fence_async_smem();
}
__device__ __forceinline__ bool mbar_test(uint32_t mb, int parity) {
    uint32_t ok;
    asm volatile("{ .reg .pred p; mbarrier.test_wait.parity.shared.b64 p, [%1], %2; selp.u32 %0, 1, 0, p; }" : "=r"(ok) : "r"(mb), "r"(parity) : "memory");
    return ok;
}
__device__ __forceinline__ void aux_control(uint32_t sb, int cta) {
    const int kg = cta / NCR_, cr = cta % NCR_;
    const int h0 = kg < 4 ? kg * 5 : 20 + (kg - 4) * 4, nh = kg < 4 ? 5 : 4;
    { int guard = 0; while (!mbar_try(sb + MBB_GO, 0)) { if (++guard > (1 << 22)) break; } }
    red_rel(&g_misc[0], 1);
    int nl = 0, nr = 0, guard = 0;
    while (nr < NSEG_) {
        bool did = false;
        if (nl < NSEG_) {
            const int st = nl % B_OX_STAGES;
            if ((nl < B_OX_STAGES || mbar_test(sb + MBB_EMPTY + 8 * st, (nl / B_OX_STAGES - 1) & 1)) &&
                ld_acq(&g_oxcnt[nl * 8 + kg]) >= (unsigned)(2 * nh)) {
                fence_async_all();
                mbar_expect(sb + MBB_FULL + 8 * st, nh * 8192);
                bulk_g2s(sb + st * B_OX_BYTES, g_ox + (size_t)(nl * NH_ + h0) * 512, nh * 8192, sb + MBB_FULL + 8 * st);
                nl++; did = true;
            }
        }
        if (nr < nl && mbar_test(sb + MBB_ST + 8 * (nr & 3), (nr >> 2) & 1)) { red_rel(&g_pcnt[nr * 8 + cr], 1); nr++; did = true; }
        if (did) guard = 0;
        else { if (++guard > (1 << 17)) { g_misc[2] = 4; break; } __nanosleep(100); }
    }
}
__device__ __forceinline__ void aux_compute(const AuxArgs& P, unsigned char* smem, uint32_t sb, int cta, int warp) {
    const bf16* __restrict__ x = P.x; const bf16* __restrict__ Wo = P.Wo; const bf16* __restrict__ Bk = P.Bk; const bf16* __restrict__ Bv = P.Bv;
    const bf16* __restrict__ shk = P.shk; const bf16* __restrict__ ssmk = P.ssmk; const bf16* __restrict__ ssmD = P.ssmD;
    const bf16* __restrict__ gatew = P.gatew; bf16* __restrict__ out = P.out;
    const int tid = threadIdx.x, lane = tid & 31;
    const int g = lane >> 2, t = lane & 3;
    const int kg = cta / NCR_, cr = cta % NCR_;
    const int h0 = kg < 4 ? kg * 5 : 20 + (kg - 4) * 4, nh = kg < 4 ? 5 : 4;
    const uint32_t mb_full = sb + MBB_FULL, mb_empty = sb + MBB_EMPTY, mb_st = sb + MBB_ST, mb_go = sb + MBB_GO;
    CAL(112 + cta, 0);
    {
        uint32_t wv[10];
#pragma unroll
        for (int i = 0; i < 10; i++) wv[i] = __ldg((const uint32_t*)gatew + lane + 32 * i);
        uint32_t xv[8][10];
#pragma unroll
        for (int j = 0; j < 8; j++) {
            const int r = min(cta * 8 + warp + j * (NB_CTAS * 8), S_ - 1);
#pragma unroll
            for (int i = 0; i < 10; i++) xv[j][i] = __ldg((const uint32_t*)(x + (size_t)r * DM_) + lane + 32 * i);
        }
#pragma unroll
        for (int j = 0; j < 8; j++) {
            const int r = cta * 8 + warp + j * (NB_CTAS * 8);
            float acc = 0.f;
#pragma unroll
            for (int i = 0; i < 10; i++) acc += rbf(bflo(xv[j][i]) * bflo(wv[i])) + rbf(bfhi(xv[j][i]) * bfhi(wv[i]));
#pragma unroll
            for (int o = 16; o; o >>= 1) acc += __shfl_xor_sync(~0u, acc, o);
            if (lane == 0 && r < S_) g_gate[r] = rbf(1.f / (1.f + __expf(-rbf(acc))));
        }
    }

    for (int item = (cta + 19) % NB_CTAS; item < 80; item += NB_CTAS) {
        const int c0 = item * 8;
        bar_sync(1, 256);
        for (int i = tid; i < 8 * 24; i += 256) sts128(sb + B_U_OFF + (i / 24) * U_STRIDE + (i % 24) * 16, make_uint4(0, 0, 0, 0));
        {
            const uint32_t krb = sb + B_KR_OFF + warp * KR_STRIDE;
            const bf16* kp = ssmk + (size_t)(c0 + warp) * S_;
            uint4 v[8]; uint32_t pv[8];
#pragma unroll
            for (int j = 0; j < 8; j++) {
                const int i = lane + 32 * j;
                v[j] = __ldg((const uint4*)kp + i);
                pv[j] = i > 0 ? __ldg((const uint32_t*)kp + 4 * i - 1) : 0u;
            }
#pragma unroll
            for (int j = 0; j < 8; j++) {
                const int i = lane + 32 * j;
                sts128(krb + (2040 - 8 * i) * 2, make_uint4(__byte_perm(v[j].w, 0, 0x1032), __byte_perm(v[j].z, 0, 0x1032),
                                                            __byte_perm(v[j].y, 0, 0x1032), __byte_perm(v[j].x, 0, 0x1032)));
                sts128(krb + 4160 + (2040 - 8 * i) * 2, make_uint4(__byte_perm(v[j].w, v[j].z, 0x7610), __byte_perm(v[j].z, v[j].y, 0x7610),
                                                                   __byte_perm(v[j].y, v[j].x, 0x7610), __byte_perm(v[j].x, pv[j], 0x7610)));
            }
            if (lane < 4) { sts128(krb + 4096 + lane * 16, make_uint4(0, 0, 0, 0)); sts128(krb + 4160 + 4096 + lane * 16, make_uint4(0, 0, 0, 0)); }
        }
        {
            float sh[8][4];
#pragma unroll
            for (int c = 0; c < 8; c++) {
                uint2 v = __ldg((const uint2*)(shk + (c0 + c) * 4));
                sh[c][0] = bflo(v.x); sh[c][1] = bfhi(v.x); sh[c][2] = bflo(v.y); sh[c][3] = bfhi(v.y);
            }
            const int t0 = tid * 8;
            uint4 kr[11], vr[8];
#pragma unroll
            for (int i = 0; i < 11; i++) { int r = t0 - 3 + i; kr[i] = r >= 0 ? __ldg((const uint4*)(Bk + (size_t)r * DM_ + c0)) : make_uint4(0, 0, 0, 0); }
#pragma unroll
            for (int i = 0; i < 8; i++) vr[i] = __ldg((const uint4*)(Bv + (size_t)(t0 + i) * DM_ + c0));
#pragma unroll
            for (int c = 0; c < 8; c++) {
                float res[8];
#pragma unroll
                for (int i = 0; i < 8; i++) {
                    float a = 0.f;
#pragma unroll
                    for (int tt = 0; tt < 4; tt++) {
                        uint32_t wd = ((const uint32_t*)&kr[i + tt])[c >> 1];
                        float kv_ = (c & 1) ? bfhi(wd) : bflo(wd);
                        a = rbf(a + rbf(kv_ * sh[c][3 - tt]));
                    }
                    uint32_t wd = ((const uint32_t*)&vr[i])[c >> 1];
                    res[i] = a * ((c & 1) ? bfhi(wd) : bflo(wd));
                }
                uint4 o = make_uint4(pack2(res[0], res[1]), pack2(res[2], res[3]), pack2(res[4], res[5]), pack2(res[6], res[7]));
                sts128(sb + B_U_OFF + c * U_STRIDE + (8 + (tid >> 1)) * 48 + (tid & 1) * 16, o);
            }
        }
        bar_sync(1, 256);
        {
            float acc[16][4];
#pragma unroll
            for (int i = 0; i < 64; i++) ((float*)acc)[i] = 0.f;
            const uint32_t kb = sb + B_KR_OFF + warp * KR_STRIDE + ((g & 1) ? (2047 - g + 2 * t) * 2 : 4160 + (2046 - g + 2 * t) * 2);
            const uint32_t ub = sb + B_U_OFF + warp * U_STRIDE + (8 + (lane & 7) + (lane >> 4) * 8) * 48 + ((lane >> 3) & 1) * 16;
#pragma unroll 1
            for (int r = 0; r < 8; r++) {
                uint32_t pa[16][3];
#pragma unroll
                for (int m = 0; m < 16; m++) {
                    const uint32_t a = kb - (16 * (r + 8 * m)) * 2;
                    pa[m][0] = lds32(a + 16); pa[m][1] = lds32(a); pa[m][2] = lds32(a - 16);
                }
#pragma unroll
                for (int d = 0; d < 16; d += 2) {
                    uint32_t b[4];
                    ldsm4(b, ub + (8 * d - r) * 48);
#pragma unroll
                    for (int m = 0; m < 16 - d; m++) mma16r(acc[m + d], pa[m][1], pa[m][2], pa[m][0], pa[m][1], b[0], b[1]);
#pragma unroll
                    for (int m = 0; m < 15 - d; m++) mma16r(acc[m + d + 1], pa[m][1], pa[m][2], pa[m][0], pa[m][1], b[2], b[3]);
                }
            }
            __syncwarp();
            const float Dv = __bfloat162float(ssmD[c0 + warp]);
            bf16* u = (bf16*)(smem + B_U_OFF + warp * U_STRIDE) + 8 * 24;
#pragma unroll
            for (int i = 0; i < 16; i++) {
#pragma unroll
                for (int q = 0; q < 4; q++) {
                    const int idx = (8 * i + 2 * t + (q & 1)) * 24 + g + (q >> 1) * 8;
                    const float kvv = __bfloat162float(u[idx]);
                    u[idx] = __float2bfloat16_rn(rbf(acc[i][q]) + rbf(kvv * Dv));
                }
            }
        }
        uint4 xv[8];
#pragma unroll
        for (int j = 0; j < 8; j++) xv[j] = __ldg((const uint4*)(x + (size_t)(tid + 256 * j) * DM_ + c0));
        bar_sync(1, 256);
#pragma unroll
        for (int j = 0; j < 8; j++) {
            const int r = tid + 256 * j;
            uint32_t o[4];
            const bf16* u = (const bf16*)(smem + B_U_OFF) + (8 + (r >> 4)) * 24 + (r & 15);
#pragma unroll
            for (int c = 0; c < 4; c++) {
                uint32_t wd = ((const uint32_t*)&xv[j])[c];
                o[c] = pack2(bflo(wd) * __bfloat162float(u[(2 * c) * (U_STRIDE / 2)]), bfhi(wd) * __bfloat162float(u[(2 * c + 1) * (U_STRIDE / 2)]));
            }
            *(uint4*)(g_b + (size_t)r * DM_ + c0) = make_uint4(o[0], o[1], o[2], o[3]);
        }
    }
    fence_async_smem();
    __syncwarp();
    if (lane == 0) mbar_arrive(mb_go);
    CAL(112 + cta, 1);

    const int wg = warp >> 2, w = warp & 3;
    const int col = cr * 128 + wg * 64 + 16 * w + 2 * g;
    uint32_t A[40][4];
#pragma unroll
    for (int ks = 0; ks < 40; ks++) {
        const int hh = ks >> 3;
        uint32_t r[4] = {0, 0, 0, 0};
        if (hh < nh) {
#pragma unroll
            for (int i = 0; i < 4; i++) {
                const int p = (ks & 7) * 16 + 2 * t + (i & 1) + (i >> 1) * 8;
                r[i] = __ldg((const uint32_t*)(Wo + (size_t)((h0 + hh) * 128 + eperm(p)) * DM_ + col));
            }
        }
        A[ks][0] = __byte_perm(r[0], r[1], 0x5410); A[ks][1] = __byte_perm(r[0], r[1], 0x7632);
        A[ks][2] = __byte_perm(r[2], r[3], 0x5410); A[ks][3] = __byte_perm(r[2], r[3], 0x7632);
    }
    CAL(112 + cta, 2);
    auto finalize = [&](int n) {
        const int r = kg + 7 * warp;
        if (r < 32) {
            if (lane == 0) {
                int guard = 0;
                while (ld_acq(&g_pcnt[n * 8 + cr]) < (unsigned)NKG_) { if (++guard > (1 << 18)) { g_misc[2] = 6; break; } __nanosleep(50); }
                if (n == 0) { guard = 0; while (ld_acq(&g_misc[0]) < (unsigned)NB_CTAS) { if (++guard > (1 << 22)) break; __nanosleep(200); } }
            }
            __syncwarp();
            const int row = n * 32 + r, c = cr * 128 + lane * 4;
            float4 v[NKG_];
#pragma unroll
            for (int k = 0; k < NKG_; k++) v[k] = __ldcg((const float4*)(g_part + ((size_t)k * S_ + row) * DM_ + c));
            const float gt = __ldcg(&g_gate[row]), og = rbf(1.f - gt);
            const uint2 bv = __ldcg((const uint2*)(g_b + (size_t)row * DM_ + c));
            float4 a = v[0];
#pragma unroll
            for (int k = 1; k < NKG_; k++) { a.x += v[k].x; a.y += v[k].y; a.z += v[k].z; a.w += v[k].w; }
            uint2 o;
            o.x = pack2(rbf(gt * rbf(a.x)) + rbf(og * bflo(bv.x)), rbf(gt * rbf(a.y)) + rbf(og * bfhi(bv.x)));
            o.y = pack2(rbf(gt * rbf(a.z)) + rbf(og * bflo(bv.y)), rbf(gt * rbf(a.w)) + rbf(og * bfhi(bv.y)));
            *(uint2*)(out + (size_t)row * DM_ + c) = o;
        }
    };
#pragma unroll 1
    for (int n = 0; n < NSEG_; n++) {
        const int st = n % B_OX_STAGES;
        { int guard = 0; while (!mbar_try(mb_full + 8 * st, (n / B_OX_STAGES) & 1)) { if (++guard > (1 << 20)) break; } }
        __syncwarp();
        float acc[16];
        const uint32_t d0 = __shfl_sync(0xffffffffu, desc_sw128(sb + st * B_OX_BYTES), 0);
        WG_FENCE();
#pragma unroll
        for (int ks = 0; ks < 32; ks++) wgmma_n32(acc, A[ks], d0 + (((ks >> 2) * 4096 + (ks & 3) * 32) >> 4), ks > 0);
        if (nh == 5) {
#pragma unroll
            for (int ks = 32; ks < 40; ks++) wgmma_n32(acc, A[ks], d0 + (((ks >> 2) * 4096 + (ks & 3) * 32) >> 4), 1);
        }
        WG_COMMIT();
        WG_WAIT0();
        if (lane == 0) mbar_arrive(mb_empty + 8 * st);
        float* pp = g_part + ((size_t)kg * S_ + n * 32) * DM_ + col;
#pragma unroll
        for (int j = 0; j < 4; j++) {
            *(float2*)(pp + (size_t)(8 * j + 2 * t) * DM_) = make_float2(acc[4 * j], acc[4 * j + 2]);
            *(float2*)(pp + (size_t)(8 * j + 2 * t + 1) * DM_) = make_float2(acc[4 * j + 1], acc[4 * j + 3]);
        }
        __syncwarp();
        if (lane == 0) mbar_arrive(mb_st + 8 * (n & 3));
        if (n >= B_LAG) finalize(n - B_LAG);
    }
    for (int n = NSEG_ - B_LAG; n < NSEG_; n++) finalize(n);
    CAL(112 + cta, 3);
    bar_sync(1, 256);
    volatile unsigned* flag = (volatile unsigned*)(smem + MBB_FLAG);
    if (tid == 0) {
        unsigned old; asm volatile("atom.acq_rel.gpu.global.add.u32 %0, [%1], 1;" : "=r"(old) : "l"(&g_misc[1]) : "memory");
        *flag = (old == NB_CTAS - 1);
    }
    bar_sync(1, 256);
    if (*flag) {
        for (int i = tid; i < NSEG_ * 8; i += 256) { g_oxcnt[i] = 0; g_pcnt[i] = 0; }
        if (tid == 0) { g_misc[0] = 0; g_misc[1] = 0; }
    }
}

constexpr int N_SPARE = 16;
__global__ void __launch_bounds__(B_THREADS, 1) aux_kernel(const AuxArgs P) {
    extern __shared__ __align__(1024) unsigned char smem[];
    const uint32_t sb = __shfl_sync(0xffffffffu, smem_u32(smem), 0);
    const int warp = __shfl_sync(0xffffffffu, threadIdx.x >> 5, 0);
    const int cta = N_SPARE + blockIdx.x;
    if (threadIdx.x == 0) aux_init(sb);
    __syncthreads();
    if (warp >= 8) {
        asm volatile("setmaxnreg.dec.sync.aligned.u32 56;");
        if (threadIdx.x == 256) aux_control(sb, cta);
    } else {
        asm volatile("setmaxnreg.inc.sync.aligned.u32 224;");
        aux_compute(P, smem, sb, cta, warp);
    }
}

constexpr int XT_OFF = 0, WO_OFF = 81920, WO_STRIDE = 464, KV_STRIDE = 272, XB_BYTES = 32 * KV_STRIDE, QX_BYTES = 16 * KV_STRIDE,
              K_OFF = 141312, V_OFF = K_OFF + 2 * XB_BYTES, EX_OFF = V_OFF + 2 * XB_BYTES  ,
              QX_OFF = EX_OFF + XB_BYTES, QF_OFF = QX_OFF + 2 * QX_BYTES, KF_OFF = QF_OFF + 2048, VF_OFF = KF_OFF + 4096,
              IN_OFF = VF_OFF + 4096, M_OFF = IN_OFF + 7680, EX2_OFF = M_OFF + 10240 + 512  ,
              BAR_OFF = EX2_OFF + XB_BYTES, A_SMEM = BAR_OFF + 144;
constexpr int O_OFF = QF_OFF;
__device__ __forceinline__ uint32_t kv_off(int which, int role, int n) {
    const int base = which == 1 ? K_OFF : V_OFF;
    if (which != role) return base + (n & 1) * XB_BYTES;
    const int j = n % 3;
    return j == 2 ? EX_OFF : base + j * XB_BYTES;
}
__device__ __forceinline__ void tile_owner(int r, int tau, int nown, int& gr, int& rk, int& sl) {
    int q = tau < 8 ? 16 + 8 * r + tau : 6 * r + tau - 8;
    sl = q >= 3 * nown; q -= 20 * sl;
    gr = q >= 2 * nown ? 2 : (q >= nown ? 1 : 0);
    rk = q - gr * nown;
}
__device__ __forceinline__ int slot_tile(int q) { return q < 16 ? 14 * (q / 6) + 8 + q % 6 : 14 * ((q - 16) >> 3) + ((q - 16) & 7); }
__host__ __device__ constexpr int korder(int i) { return i < 24 ? 14 * (i >> 3) + (i & 7) : 14 * ((i - 24) / 6) + 8 + (i - 24) % 6; }
constexpr int MB_X = BAR_OFF  , MB_M = BAR_OFF + 16  , MB_IN = BAR_OFF + 40  , MB_QC = BAR_OFF + 120, MB_H1 = BAR_OFF + 64,
              MB_KV = BAR_OFF + 72  , MB_FREE = BAR_OFF + 88  , MB_XD = BAR_OFF + 104  , MB_WO = BAR_OFF + 128;
constexpr float SCALE = 0.08838834764831845f;
constexpr float LOG2E = 1.4426950408889634f;
constexpr int A_THREADS = 384, A_CTAS = 112;

#define FRESH_LANE() int lane = lane_r; asm volatile("" : "+r"(lane)); const int g = lane >> 2, t = lane & 3; const uint32_t l16 = lane * 16; (void)g; (void)t; (void)l16
#define PIN(x) asm volatile("" ::"r"(x))
#define TS(i) do {} while (0)
#define TSV(i, cond, val) do {} while (0)

__global__ void __launch_bounds__(A_THREADS, 1)
rec_kernel(const __grid_constant__ CUtensorMap tmx, const bf16* __restrict__ mem0, const bf16* __restrict__ Wq,
           const bf16* __restrict__ Wk, const bf16* __restrict__ Wv, const bf16* __restrict__ Wo, const AuxArgs P) {
    extern __shared__ __align__(1024) unsigned char smem[];
    const uint32_t sb = __shfl_sync(0xffffffffu, smem_u32(smem), 0);
    const int tid = threadIdx.x, warp = __shfl_sync(0xffffffffu, tid >> 5, 0);
    const int lane = tid & 31;
    const int g = lane >> 2, t = lane & 3;
    uint32_t rank; asm volatile("mov.u32 %0, %%cluster_ctarank;" : "=r"(rank));
    const int cl = blockIdx.x >> 4;
    const int nh = cl < 4 ? 5 : 4;
    const int hl = rank / 3, role = rank - 3 * hl, tb = 3 * hl;
    const int head = (cl < 4 ? 5 * cl : 20 + 4 * (cl - 4)) + hl;
    const bool is_head = hl < nh;
    const int nown = 3 * nh;

    const int worker = cl < 4 ? cl : 4 + (cl - 4) * 4 + ((int)rank - 12);
    asm volatile("griddepcontrol.launch_dependents;");
    CAL(blockIdx.x, 0);
    if (tid == 0) {
        mbar_init(sb + MB_X, 1); mbar_init(sb + MB_X + 8, 1);
        for (int j = 0; j < 3; j++) mbar_init(sb + MB_M + 8 * j, 1);
        mbar_init(sb + MB_IN, 1); mbar_init(sb + MB_IN + 8, 1); mbar_init(sb + MB_IN + 16, 1); mbar_init(sb + MB_QC, 3);
        mbar_init(sb + MB_H1, 1); mbar_init(sb + MB_KV, 1); mbar_init(sb + MB_KV + 8, 1);
        mbar_init(sb + MB_FREE, 2); mbar_init(sb + MB_FREE + 8, 2); mbar_init(sb + MB_XD, 8); mbar_init(sb + MB_XD + 8, 8); mbar_init(sb + MB_WO, 96);
        asm volatile("fence.mbarrier_init.release.cluster;" ::: "memory");
        fence_async_smem();
        mbar_expect(sb + MB_X, 40960); mbar_expect(sb + MB_X + 8, 40960);
        if (!is_head) aux_init(sb);
    }
    __syncthreads();
    cluster_sync();
    const uint16_t tmask = (uint16_t)(7u << tb);
    if (tid == 0 && is_head) {
        for (int n = 0; n < 2; n++)
            for (int kb = role; kb < 10; kb += 3) tma3d_mc(sb + XT_OFF + n * 40960 + kb * 4096, &tmx, 0, 32 * n, kb, sb + MB_X + 8 * n, tmask);
    }

    if (warp < 8) {
        asm volatile("setmaxnreg.inc.sync.aligned.u32 224;");
        if (is_head) {
        const int lane_r = __shfl_sync(0xffffffffu, tid & 31, tid & 31);
        const int wg = warp >> 2, w = warp & 3;
        uint32_t A[40][4];
        {
            const bf16* W = role == 0 ? Wq : (role == 1 ? Wk : Wv);
            const bf16* wp = W + (size_t)(2 * t) * 4096 + head * 128 + 16 * warp + 2 * g;
#pragma unroll
            for (int ks = 0; ks < 40; ks++) {
                A[ks][0] = __ldg((const uint32_t*)(wp + (size_t)(16 * ks) * 4096));
                A[ks][1] = __ldg((const uint32_t*)(wp + (size_t)(16 * ks + 1) * 4096));
                A[ks][2] = __ldg((const uint32_t*)(wp + (size_t)(16 * ks + 8) * 4096));
                A[ks][3] = __ldg((const uint32_t*)(wp + (size_t)(16 * ks + 9) * 4096));
            }
#pragma unroll
            for (int ks = 0; ks < 40; ks++) {
                const uint32_t r0 = A[ks][0], r1 = A[ks][1], r2 = A[ks][2], r3 = A[ks][3];
                A[ks][0] = __byte_perm(r0, r1, 0x5410); A[ks][1] = __byte_perm(r0, r1, 0x7632);
                A[ks][2] = __byte_perm(r2, r3, 0x5410); A[ks][3] = __byte_perm(r2, r3, 0x7632);
            }
        }

        auto xproj = [&](int n) {
            const int st = n & 1;
            FRESH_LANE();
            const uint32_t a = sb + (role == 0 ? (st ? EX2_OFF : EX_OFF) : kv_off(role, role, n)) + (8 * (lane >> 4) + (lane & 7)) * KV_STRIDE + 32 * warp + ((lane >> 3) & 1) * 16;
            PIN(a);
            if (role == 0) { if (n >= 2) mbar_wait_u(sb + MB_QC, st); }
            else if (n >= 3) mbar_wait_u(sb + MB_FREE + 8 * ((n - 3) & 1), ((n - 3) >> 1) & 1);
            mbar_wait_u(sb + MB_X + 8 * st, (n >> 1) & 1);
            float acc[16];
            const uint32_t d0 = __shfl_sync(0xffffffffu, desc_sw128(sb + XT_OFF + st * 40960), 0);
            WG_FENCE();
#pragma unroll
            for (int ks = 0; ks < 40; ks++) wgmma_n32(acc, A[ks], d0 + (((ks >> 2) * 4096 + (ks & 3) * 32) >> 4), ks > 0);
            WG_COMMIT();
            WG_WAIT0();
            stsm4t(a, pack2(acc[0], acc[1]), pack2(acc[2], acc[3]), pack2(acc[4], acc[5]), pack2(acc[6], acc[7]));
            stsm4t(a + 16 * KV_STRIDE, pack2(acc[8], acc[9]), pack2(acc[10], acc[11]), pack2(acc[12], acc[13]), pack2(acc[14], acc[15]));
            fence_async_smem();
            __syncwarp();
            if (lane == 0) mbar_arrive(sb + MB_XD + 8 * st);
        };

        xproj(0);
        xproj(1);
#pragma unroll 1
        for (int s = 0; s < NSEG_; s++) {
            const int st = s & 1;
            if (warp == 4 && lane_r == 0) mbar_expect(sb + MB_H1, 6144);
            {
                float acc[4][4];
#pragma unroll
                for (int i = 0; i < 16; i++) ((float*)acc)[i] = 0.f;
                FRESH_LANE();
                const uint32_t mrd = sb + M_OFF + lane * 8;
                const uint32_t dl = sb + (role == 0 ? QF_OFF : (role == 1 ? KF_OFF : VF_OFF) + st * 2048) + warp * 256 + lane * 8;
                PIN(mrd); PIN(dl);
                mbar_wait_u(sb + MB_M, st);
                TS(0);
                uint2 b[40];
#pragma unroll
                for (int i = 0; i < 12; i++) b[i] = lds64(mrd + korder(i) * 256);
#pragma unroll
                for (int i = 0; i < 40; i++) {
                    if (i == LOOKW) {
                        mbar_wait_u(sb + MB_M + 8, st);
#pragma unroll
                        for (int k = 24; k < LOOKW + 12; k++) b[k] = lds64(mrd + korder(k) * 256);
                    }
                    if (i + 12 < 40 && (i + 12 < 24 || i >= LOOKW)) b[i + 12] = lds64(mrd + korder(i + 12) * 256);
                    mma16(acc[i & 3], A[korder(i)], b[i].x, b[i].y);
                }
                TS(1);
                uint32_t u0 = pack2((acc[0][0] + acc[1][0]) + (acc[2][0] + acc[3][0]), (acc[0][1] + acc[1][1]) + (acc[2][1] + acc[3][1]));
                uint32_t u1 = pack2((acc[0][2] + acc[1][2]) + (acc[2][2] + acc[3][2]), (acc[0][3] + acc[1][3]) + (acc[2][3] + acc[3][3]));
                if (role != 2) { u0 = movm(u0); u1 = movm(u1); }
#pragma unroll
                for (int r = 0; r < 3; r++) st_async8(mapa(dl, tb + r), u0, u1, mapa(sb + MB_H1, tb + r));
            }
            TS(2);
            if (s == NSEG_ - 1) break;
            if (s == 0) mbar_wait_u(sb + MB_WO, 0);
            uint32_t wa[8][4];
            const bool pair = wg || (w >= 2 && role != 2);
            const int tileB = wg ? 8 + w : 10 + w;
            int wA, rA, sA, wB, rB, sB;
            tile_owner(role, warp, nown, wA, rA, sA); tile_owner(role, tileB, nown, wB, rB, sB);
            uint32_t wl, inA, inB;
            {
                FRESH_LANE();
                wl = sb + WO_OFF + ((lane & 7) + (lane >> 4) * 8) * WO_STRIDE + ((lane >> 3) & 1) * 16;
                inA = mapa(sb + IN_OFF + (wA * 2 + sA) * 1280 + hl * 256, rA); inB = mapa(sb + IN_OFF + wB * 2560 + hl * 256, rB);
                PIN(wl);
            }
            if (wg) {
                FRESH_LANE();
#pragma unroll
                for (int ks = 0; ks < 8; ks++) ldsm4t(wa[ks], wl + warp * 32 + ks * 16 * WO_STRIDE);
                if (w < 2) {
                    mbar_wait_u(sb + MB_H1, st);
                    if (lane == 0) {
                        if (w == 0) {
                            mbar_expect(sb + MB_M, 6144); mbar_expect(sb + MB_M + 8, 4096);
                        }
                        else {
                            for (int n = (s == 0 ? 2 : s + 3); n <= s + 3 && n < NSEG_; n++) {
                                mbar_expect(sb + MB_X + 8 * (n & 1), 40960);
                                for (int kb = role; kb < 10; kb += 3)
                                    tma3d_mc(sb + XT_OFF + (n & 1) * 40960 + kb * 4096, &tmx, 0, 32 * n, kb, sb + MB_X + 8 * (n & 1), tmask);
                            }
                        }
                    }
                    __syncwarp();
                }
            } else {
                FRESH_LANE();
                const uint32_t s_base = sb + M_OFF + role * 3584;
                const uint32_t r8 = (lane & 7) * KV_STRIDE;
                const int mt = w & 1, eh = w >> 1;
                mbar_wait_u(sb + MB_KV + 8 * st, (s >> 1) & 1);
                if (w == 3 && lane == 0) asm volatile("mbarrier.arrive.relaxed.cluster.shared::cluster.b64 _, [%0];" ::"r"(mapa(sb + MB_QC, tb)) : "memory");
                uint32_t vb[2][2][4];
                uint2 vm[2];
                {
                    const uint32_t ka = sb + kv_off(1, role, s) + eh * 128 + r8 + (16 * mt + ((lane >> 3) & 1) * 8) * KV_STRIDE + (lane >> 4) * 16;
                    const uint32_t fl = sb + lane * 8;
                    const uint32_t sw = s_base + eh * 1280 + mt * 64 + t * 320 + g * 4;
                    const uint32_t sm = s_base + 2560 + w * 256 + t * 64 + g * 4;
                    uint32_t a[4][4];
#pragma unroll
                    for (int k = 0; k < 4; k++) ldsm4(a[k], ka + k * 32);
                    const uint32_t va1 = sb + kv_off(2, role, s) + w * 64 + r8 + ((lane >> 3) & 1) * 8 * KV_STRIDE + (lane >> 4) * 16;
                    ldsm4t(vb[0][0], va1); ldsm4t(vb[0][1], va1 + 32);
                    ldsm4t(vb[1][0], va1 + 16 * KV_STRIDE); ldsm4t(vb[1][1], va1 + 16 * KV_STRIDE + 32);
                    PIN(fl); PIN(sw); PIN(sm);
                    mbar_wait_u(sb + MB_H1, st);
                    TS(3);
                    uint2 b[4], am[2], bm[2];
#pragma unroll
                    for (int k = 0; k < 4; k++) b[k] = lds64(fl + QF_OFF + (4 * eh + k) * 256);
#pragma unroll
                    for (int k = 0; k < 2; k++) { am[k] = lds64(fl + KF_OFF + st * 2048 + (2 * w + k) * 256); bm[k] = lds64(fl + QF_OFF + (2 * w + k) * 256); }
                    float c0[4] = {0, 0, 0, 0}, c1[4] = {0, 0, 0, 0}, c2[4] = {0, 0, 0, 0}, c3[4] = {0, 0, 0, 0};
                    mma16(c0, a[0], b[0].x, b[0].y); mma16(c1, a[1], b[1].x, b[1].y);
                    mma16r(c2, am[0].x, 0u, am[0].y, 0u, bm[0].x, bm[0].y);
                    mma16r(c3, am[1].x, 0u, am[1].y, 0u, bm[1].x, bm[1].y);
                    mma16(c0, a[2], b[2].x, b[2].y); mma16(c1, a[3], b[3].x, b[3].y);
                    sts32f(sm, c2[0] + c3[0]); sts32f(sm + 32, c2[1] + c3[1]);
                    sts32f(sw, c0[0] + c1[0]); sts32f(sw + 160, c0[1] + c1[1]);
                    sts32f(sw + 32, c0[2] + c1[2]); sts32f(sw + 160 + 32, c0[3] + c1[3]);
#pragma unroll
                    for (int k = 0; k < 2; k++) vm[k] = lds64(fl + VF_OFF + st * 2048 + (2 * w + k) * 256);
                }
                const uint32_t sr = s_base + g * 160 + t * 8;
                bar_sync(7, 128);
                TS(4);
                float sc[10];
                {
                    float2 m[4], p0[4], p1[4];
#pragma unroll
                    for (int j = 0; j < 4; j++) { p0[j] = lds64f(sr + j * 32); p1[j] = lds64f(sr + 1280 + j * 32); }
#pragma unroll
                    for (int j = 0; j < 4; j++) m[j] = lds64f(s_base + 2560 + j * 256 + lane * 8);
#pragma unroll
                    for (int j = 0; j < 4; j++) { sc[2 + 2 * j] = p0[j].x + p1[j].x; sc[3 + 2 * j] = p0[j].y + p1[j].y; }
                    sc[0] = (m[0].x + m[1].x) + (m[2].x + m[3].x); sc[1] = (m[0].y + m[1].y) + (m[2].y + m[3].y);
                }
                float mx = fmaxf(fmaxf(fmaxf(sc[2], sc[3]), fmaxf(sc[4], sc[5])), fmaxf(fmaxf(sc[6], sc[7]), fmaxf(sc[8], sc[9])));
                mx = fmaxf(mx, fmaxf(sc[0], sc[1]));
                mx = fmaxf(mx, __shfl_xor_sync(~0u, mx, 1)); mx = fmaxf(mx, __shfl_xor_sync(~0u, mx, 2));
                const float nm = -mx * (SCALE * LOG2E);
#pragma unroll
                for (int i = 0; i < 10; i++) sc[i] = ex2(fmaf(sc[i], SCALE * LOG2E, nm));
                uint32_t p[5];
#pragma unroll
                for (int j = 0; j < 5; j++) p[j] = pack2(sc[2 * j], sc[2 * j + 1]);
                float o[4][4];
#pragma unroll
                for (int i = 0; i < 16; i++) ((float*)o)[i] = 0.f;
#pragma unroll
                for (int n = 0; n < 4; n++) mma8(o[n], p[0], 0u, (n & 1) ? vm[n >> 1].y : vm[n >> 1].x);
#pragma unroll
                for (int n = 0; n < 4; n++) mma16r(o[n], p[1], 0u, p[2], 0u, vb[0][n >> 1][2 * (n & 1)], vb[0][n >> 1][2 * (n & 1) + 1]);
#pragma unroll
                for (int n = 0; n < 4; n++) mma16r(o[n], p[3], 0u, p[4], 0u, vb[1][n >> 1][2 * (n & 1)], vb[1][n >> 1][2 * (n & 1) + 1]);
                float sum = ((sc[0] + sc[1]) + (sc[2] + sc[3])) + ((sc[4] + sc[5]) + (sc[6] + sc[7])) + (sc[8] + sc[9]);
                sum += __shfl_xor_sync(~0u, sum, 1); sum += __shfl_xor_sync(~0u, sum, 2);
                const float inv = rcp(sum);
                sts128(sb + O_OFF + w * 512 + l16,
                       make_uint4(pack2(o[0][0] * inv, o[0][1] * inv), pack2(o[1][0] * inv, o[1][1] * inv),
                                  pack2(o[2][0] * inv, o[2][1] * inv), pack2(o[3][0] * inv, o[3][1] * inv)));
#pragma unroll
                for (int ks = 0; ks < 8; ks++) ldsm4t(wa[ks], wl + warp * 32 + ks * 16 * WO_STRIDE);
            }
            {
            FRESH_LANE();
            bar_sync(1, 256);
            TS(5);
            uint4 ob[4];
#pragma unroll
            for (int k = 0; k < 4; k++) ob[k] = lds128(sb + O_OFF + k * 512 + l16);
            float d[2][4];
#pragma unroll
            for (int i = 0; i < 8; i++) ((float*)d)[i] = 0.f;
#pragma unroll
            for (int k = 0; k < 4; k++) {
                mma16(d[0], wa[2 * k], ob[k].x, ob[k].y); mma16(d[1], wa[2 * k + 1], ob[k].z, ob[k].w);
                if (pair) { ldsm4t(wa[2 * k], wl + tileB * 32 + (2 * k) * 16 * WO_STRIDE); ldsm4t(wa[2 * k + 1], wl + tileB * 32 + (2 * k + 1) * 16 * WO_STRIDE); }
            }
            st_async8(inA + lane * 8, pack2(d[0][0] + d[1][0], d[0][1] + d[1][1]), pack2(d[0][2] + d[1][2], d[0][3] + d[1][3]), mapa(sb + MB_IN + 8 * wA, rA));
            if (pair) {
#pragma unroll
                for (int i = 0; i < 8; i++) ((float*)d)[i] = 0.f;
#pragma unroll
                for (int k = 0; k < 4; k++) { mma16(d[0], wa[2 * k], ob[k].x, ob[k].y); mma16(d[1], wa[2 * k + 1], ob[k].z, ob[k].w); }
                st_async8(inB + lane * 8, pack2(d[0][0] + d[1][0], d[0][1] + d[1][1]), pack2(d[0][2] + d[1][2], d[0][3] + d[1][3]), mapa(sb + MB_IN + 8 * wB, rB));
            }
            }
            TS(6);
            TSV(14, threadIdx.x == 224, clk());
            if (s + 2 < NSEG_) xproj(s + 2);
            TS(7);
        }
        if (warp == 0) { mbar_wait_u(sb + MB_H1, 1); mbar_wait_u(sb + MB_KV + 8, 1); mbar_wait_u(sb + MB_FREE, 1); mbar_wait_u(sb + MB_FREE + 8, 1); if (role == 0) mbar_wait_u(sb + MB_QC, 0); }
        }
        else aux_compute(P, smem, sb, worker, warp);
    } else {
      asm volatile("setmaxnreg.dec.sync.aligned.u32 56;");
      if (warp < 11) {
        const int cw = warp - 8, ct = cw * 32 + lane;
        const int q = cw * nown + (int)rank, idx = rank;
        const bool own = is_head && q < 40;
        const int T = slot_tile(q);
        const bool own2 = own && q >= 16 && q + 20 >= 3 * nown && q + 20 < 40;
        const int dT = own2 ? slot_tile(q + 20) - T : 0;
        if (own) st_rel8(&g_X[2][(T * 7 + cl) * 32 + lane], 0u, 0u);
        if (own2) st_rel8(&g_X[2][((T + dT) * 7 + cl) * 32 + lane], 0u, 0u);
        if (is_head) {
            uint2 mv[14];
#pragma unroll
            for (int j = 0; j < 14; j++) {
                const int p = min(ct + 96 * j, 1279), ks = p >> 5, l = p & 31;
                const uint32_t* mp = (const uint32_t*)(mem0 + (l >> 2) * DM_ + ks * 16 + 2 * (l & 3));
                mv[j] = make_uint2(__ldg(mp), __ldg(mp + 4));
            }
            const int nch = role == 2 ? 24 : 28;
            for (int r = cw; r < 128; r += 3) {
                if (lane < nch) cp_async16(sb + WO_OFF + r * WO_STRIDE + lane * 16, Wo + (size_t)(head * 128 + eperm(r)) * DM_ + role * 224 + lane * 8);
            }
            asm volatile("cp.async.mbarrier.arrive.noinc.shared.b64 [%0];" ::"r"(sb + MB_WO) : "memory");
#pragma unroll
            for (int j = 0; j < 14; j++) {
                const int p = min(ct + 96 * j, 1279);
                sts64(sb + M_OFF + p * 8, mv[j].x, mv[j].y);
            }
            bar_sync(6, 96);
            if (ct == 0) { mbar_arrive(sb + MB_M); mbar_arrive(sb + MB_M + 8); }
        }
        __threadfence();
        const bool sender = is_head && cw == 2;
        auto send_x = [&](int n) {
            const int st = n & 1;
            mbar_wait_u(sb + MB_XD + 8 * st, (n >> 1) & 1);
            if (n >= 1) mbar_wait_u(sb + MB_H1, (n - 1) & 1);
            if (n >= 2) mbar_wait_u(sb + MB_FREE + 8 * st, ((n - 2) >> 1) & 1);
            const int a0 = (2 * n) % 3, a1 = (2 * n + 1) % 3;
            const uint32_t mbkv = sb + MB_KV + 8 * st, qs = sb + (st ? EX2_OFF : EX_OFF);
            if (lane == 0) {
                if (role == 0) {
                    if (a0 != 0) bulk_s2s(mapa(sb + QX_OFF + st * QX_BYTES, tb + a0), qs, QX_BYTES, mapa(mbkv, tb + a0));
                    if (a1 != 0) bulk_s2s(mapa(sb + QX_OFF + st * QX_BYTES, tb + a1), qs + QX_BYTES, QX_BYTES, mapa(mbkv, tb + a1));
                } else {
                    const uint32_t src = sb + kv_off(role, role, n), dst = sb + kv_off(role, 0, n);
                    bulk_s2s(mapa(dst, tb), src, XB_BYTES, mapa(mbkv, tb));
                    bulk_s2s(mapa(dst, tb + 3 - role), src, XB_BYTES, mapa(mbkv, tb + 3 - role));
                }
            }
            if (role == 0 && (a0 == 0 || a1 == 0)) {
                const uint32_t src = qs + (a0 == 0 ? 0 : QX_BYTES);
                for (int i = lane; i < QX_BYTES / 16; i += 32) sts128(sb + QX_OFF + st * QX_BYTES + i * 16, lds128(src + i * 16));
            }
            __syncwarp();
            if (lane == 0) mbar_expect(mbkv, (role == 0 ? 2 * XB_BYTES : XB_BYTES) + (role != 0 && (a0 == role || a1 == role) ? QX_BYTES : 0));
            __syncwarp();
        };
        if (sender) send_x(0);
        auto owner_loop = [&](auto ntc) {
            constexpr int NT = decltype(ntc)::value;
            const uint32_t mdst = sb + M_OFF + T * 256 + lane * 8;
            const uint32_t mbar = sb + MB_M + (q < 16 ? 8 : 0);
            if (own && lane == 0) mbar_expect(sb + MB_IN + 8 * cw, NT * nh * 256);
#pragma unroll 1
            for (int s = 0; s < NSEG_ - 1; s++) {
                if (sender) send_x(s + 1);
                if (!own) continue;
                int lane_o = lane;
                asm volatile("" : "+r"(lane_o));
                uint2* xs = &g_X[s & 3][T * 7 * 32 + lane_o];
                uint2* xw = xs + cl * 32;
                const uint32_t ib = sb + IN_OFF + cw * 2560 + lane_o * 8;
                asm volatile("" ::"l"(xw), "r"(ib));
                mbar_wait_u(sb + MB_IN + 8 * cw, s & 1);
                TS(10);
                uint2 v[NT][7];
#pragma unroll
                for (int u = 0; u < NT; u++) {
                    uint2 q[5];
#pragma unroll
                    for (int h = 0; h < 4; h++) q[h] = lds64(ib + u * 1280 + h * 256);
                    q[4] = make_uint2(0, 0);
                    if (NT == 1 && nh == 5) q[4] = lds64(ib + 1024);
#define SUM5(f, c) ((f(q[0].c) + f(q[1].c)) + (f(q[2].c) + f(q[3].c)) + f(q[4].c))
                    const uint32_t o0 = nzw(pack2(SUM5(bflo, x), SUM5(bfhi, x))), o1 = nzw(pack2(SUM5(bflo, y), SUM5(bfhi, y)));
                    st_rel8(xw + u * dT * (7 * 32), o0, o1);
#pragma unroll
                    for (int c = 0; c < 7; c++) v[u][c] = c == cl ? make_uint2(o0, o1) : make_uint2(0, 0);
                }
                const int tw = clk();
                TS(11);
                if (lane == 0) mbar_expect(sb + MB_IN + 8 * cw, NT * nh * 256);
                while (clk() - tw < DELAY_X) {}
                int guard = 0;
                {
                    while (true) {
                        uint32_t chk = 0xffffffffu;
#pragma unroll
                        for (int u = 0; u < NT; u++)
#pragma unroll
                            for (int c = 0; c < 7; c++) if (min(v[u][c].x, v[u][c].y) == 0) v[u][c] = ld_poll8(xs + u * dT * (7 * 32) + c * 32);
#pragma unroll
                        for (int u = 0; u < NT; u++)
#pragma unroll
                            for (int c = 0; c < 7; c++) chk = min(chk, min(v[u][c].x, v[u][c].y));
                        if (!__any_sync(~0u, chk == 0)) break;
                        if (++guard > SPIN_LIMIT) { g_misc[2] = 2; break; }
                    }
                }
                TS(12);
#pragma unroll
                for (int u = 0; u < NT; u++) {
#define SUM7(f, c) (((f(v[u][0].c) + f(v[u][1].c)) + (f(v[u][2].c) + f(v[u][3].c))) + ((f(v[u][4].c) + f(v[u][5].c)) + f(v[u][6].c)))
                    const uint32_t b0 = movm(pack2(SUM7(bflo, x), SUM7(bfhi, x))), b1 = movm(pack2(SUM7(bflo, y), SUM7(bfhi, y)));
                    int d = idx;
#pragma unroll
                    for (int r = 0; r < (NT == 2 ? 12 : 15); r++) {
                        if (r < 12 || nh == 5) st_async8(mapa(mdst + u * dT * 256, d), b0, b1, mapa(mbar, d));
                        d = d + 1 == nown ? 0 : d + 1;
                    }
                }
                TS(13);
                TSV(15, threadIdx.x == 256, guard);
                if (s > 0) {
#pragma unroll
                    for (int u = 0; u < NT; u++) st_rel8(&g_X[(s - 1) & 3][((T + dT * u) * 7 + cl) * 32 + lane_o], 0u, 0u);
                    __threadfence();
                }
            }
        };
        if (own2) owner_loop(std::integral_constant<int, 2>());
        else if (own || sender) owner_loop(std::integral_constant<int, 1>());
      } else if (is_head) {
        unsigned* cnt = &g_oxcnt[cl];
        int pending = -1;
#pragma unroll 1
        for (int task = role; task < 2 * NSEG_; task += 3) {
            const int s = task >> 1, mt = task & 1;
            const int st = s & 1;
            mbar_wait_u(sb + MB_KV + 8 * st, (s >> 1) & 1);
            mbar_wait_u(sb + MB_H1, st);
            TS(8);
            int lane = threadIdx.x & 31;
            asm volatile("" : "+r"(lane));
            const int g = lane >> 2, t = lane & 3;
            float sc[5][4];
#pragma unroll
            for (int i = 0; i < 20; i++) ((float*)sc)[i] = 0.f;
            const uint32_t r8 = (lane & 7) * KV_STRIDE;
            {
                const uint32_t qa = sb + QX_OFF + st * QX_BYTES + ((lane >> 3) & 1) * 8 * KV_STRIDE + r8 + (lane >> 4) * 16;
                const uint32_t ka = sb + kv_off(1, role, s) + r8 + ((lane >> 3) & 1) * 16 + (lane >> 4) * 8 * KV_STRIDE;
                const uint32_t kf = sb + KF_OFF + st * 2048 + lane * 8;
                uint32_t a[2][4], b0[2][4], b1[2][4]; uint2 bm[2];
                ldsm4(a[0], qa); bm[0] = lds64(kf); ldsm4(b0[0], ka); ldsm4(b1[0], ka + 16 * KV_STRIDE);
#pragma unroll
                for (int ks = 0; ks < 8; ks++) {
                    const int c = ks & 1, n = c ^ 1;
                    if (ks < 7) {
                        ldsm4(a[n], qa + (ks + 1) * 32); bm[n] = lds64(kf + (ks + 1) * 256);
                        ldsm4(b0[n], ka + (ks + 1) * 32); ldsm4(b1[n], ka + 16 * KV_STRIDE + (ks + 1) * 32);
                    }
                    mma16(sc[0], a[c], bm[c].x, bm[c].y);
                    mma16(sc[1], a[c], b0[c][0], b0[c][1]); mma16(sc[2], a[c], b0[c][2], b0[c][3]);
                    if (mt) { mma16(sc[3], a[c], b1[c][0], b1[c][1]); mma16(sc[4], a[c], b1[c][2], b1[c][3]); }
                }
            }
            if (pending >= 0) { if (lane == 0) red_rel(cnt + pending * 8, 1); pending = -1; __syncwarp(); }
            uint32_t p[5][2];
#pragma unroll
            for (int h = 0; h < 2; h++) {
                const int lim = 8 + 16 * mt + g + 8 * h - 2 * t;
                float mx = -3.0e38f;
#pragma unroll
                for (int j = 0; j < 5; j++) {
                    uint32_t r1 = pack2(sc[j][2 * h], sc[j][2 * h + 1]);
                    r1 = pack2(bflo(r1) * SCALE, bfhi(r1) * SCALE);
                    const float v0 = (8 * j <= lim) ? bflo(r1) : -1.0e9f, v1 = (8 * j + 1 <= lim) ? bfhi(r1) : -1.0e9f;
                    sc[j][2 * h] = v0; sc[j][2 * h + 1] = v1; mx = fmaxf(mx, fmaxf(v0, v1));
                }
                mx = fmaxf(mx, __shfl_xor_sync(~0u, mx, 1)); mx = fmaxf(mx, __shfl_xor_sync(~0u, mx, 2));
                float sum = 0.f;
#pragma unroll
                for (int j = 0; j < 5; j++) {
#pragma unroll
                    for (int i = 0; i < 2; i++) { float e = ex2((sc[j][2 * h + i] - mx) * LOG2E); sc[j][2 * h + i] = e; sum += e; }
                }
                sum += __shfl_xor_sync(~0u, sum, 1); sum += __shfl_xor_sync(~0u, sum, 2);
                const float inv = rcp(sum);
#pragma unroll
                for (int j = 0; j < 5; j++) p[j][h] = pack2(sc[j][2 * h] * inv, sc[j][2 * h + 1] * inv);
            }
            uint32_t* og = (uint32_t*)(g_ox + (size_t)(s * NH_ + head) * 512) + (16 * mt + g) * 32 + t;
            const uint32_t va = sb + kv_off(2, role, s) + r8 + ((lane >> 3) & 1) * 8 * KV_STRIDE + (lane >> 4) * 16;
            const uint32_t vf = sb + VF_OFF + st * 2048 + lane * 8;
            {
                uint32_t b0[2][4], b1[2][4]; uint2 bm[2];
                bm[0] = lds64(vf); ldsm4t(b0[0], va); ldsm4t(b1[0], va + 16 * KV_STRIDE);
#pragma unroll
                for (int np = 0; np < 8; np++) {
                    const int c = np & 1, nx = c ^ 1;
                    if (np < 7) { bm[nx] = lds64(vf + (np + 1) * 256); ldsm4t(b0[nx], va + (np + 1) * 32); ldsm4t(b1[nx], va + 16 * KV_STRIDE + (np + 1) * 32); }
                    float o[2][4] = {{0, 0, 0, 0}, {0, 0, 0, 0}};
                    mma8(o[0], p[0][0], p[0][1], bm[c].x); mma8(o[1], p[0][0], p[0][1], bm[c].y);
                    mma16r(o[0], p[1][0], p[1][1], p[2][0], p[2][1], b0[c][0], b0[c][1]);
                    mma16r(o[1], p[1][0], p[1][1], p[2][0], p[2][1], b0[c][2], b0[c][3]);
                    if (mt) {
                        mma16r(o[0], p[3][0], p[3][1], p[4][0], p[4][1], b1[c][0], b1[c][1]);
                        mma16r(o[1], p[3][0], p[3][1], p[4][0], p[4][1], b1[c][2], b1[c][3]);
                    }
#pragma unroll
                    for (int n = 0; n < 2; n++) {
                        const int ch = (2 * np + n) & 7;
                        int gx = g; asm volatile("" : "+r"(gx));
                        uint32_t* o2 = og + (np >> 2) * 1024 + ((ch ^ gx) << 2);
                        o2[0] = pack2(o[n][0], o[n][1]);
                        o2[256] = pack2(o[n][2], o[n][3]);
                    }
                }
            }
            __syncwarp();
            if (lane < 3) asm volatile("mbarrier.arrive.relaxed.cluster.shared::cluster.b64 _, [%0];" ::"r"(mapa(sb + MB_FREE + 8 * st, tb + lane)) : "memory");
            if (mt == 0 && task + 3 < 2 * NSEG_) pending = s;
            else if (lane == 0) red_rel(cnt + s * 8, 1);
            __syncwarp();
            TS(9);
        }
      }
      else if (lane == 0) aux_control(sb, worker);
    }
    __syncthreads();
    CAL(blockIdx.x, 1);
    cluster_sync();
}

__device__ bf16 f_mem[2][8 * DM_];
__device__ bf16 f_qkv[3][40 * 4096];
__device__ bf16 f_o[40 * 4096];
__global__ void fb_conv(const AuxArgs P) {
    __shared__ float u[S_], kk[S_];
    const int c = blockIdx.x;
    for (int t = threadIdx.x; t < S_; t += 256) {
        float a = 0.f;
        for (int tt = 0; tt < 4; tt++) { const int r = t + tt - 3; const float kv = r >= 0 ? __bfloat162float(P.Bk[(size_t)r * DM_ + c]) : 0.f; a = rbf(a + rbf(kv * __bfloat162float(P.shk[c * 4 + 3 - tt]))); }
        u[t] = rbf(a * __bfloat162float(P.Bv[(size_t)t * DM_ + c])); kk[t] = __bfloat162float(P.ssmk[(size_t)c * S_ + t]);
    }
    __syncthreads();
    const float D = __bfloat162float(P.ssmD[c]);
    for (int t = threadIdx.x; t < S_; t += 256) {
        float y = 0.f;
        for (int j = 0; j <= t; j++) y = fmaf(u[j], kk[t - j], y);
        g_b[(size_t)t * DM_ + c] = __float2bfloat16_rn(__bfloat162float(P.x[(size_t)t * DM_ + c]) * rbf(rbf(y) + rbf(u[t] * D)));
    }
}
__global__ void fb_proj(const bf16* x, const bf16* mem, const bf16* Wq, const bf16* Wk, const bf16* Wv, int s) {
    __shared__ bf16 h[40][DM_ / 2];
    const bf16* W = blockIdx.y == 0 ? Wq : (blockIdx.y == 1 ? Wk : Wv);
    const int col = blockIdx.x * 128 + threadIdx.x;
    float acc[40];
    for (int r = 0; r < 40; r++) acc[r] = 0.f;
    for (int half = 0; half < 2; half++) {
        __syncthreads();
        for (int i = threadIdx.x; i < 40 * 320; i += 128) { const int r = i / 320, d = i % 320 + half * 320; h[r][i % 320] = r < 8 ? mem[r * DM_ + d] : x[(size_t)(s * 32 + r - 8) * DM_ + d]; }
        __syncthreads();
        for (int d = 0; d < 320; d++) {
            const float wv = __bfloat162float(W[(size_t)(d + half * 320) * 4096 + col]);
#pragma unroll
            for (int r = 0; r < 40; r++) acc[r] = fmaf(__bfloat162float(h[r][d]), wv, acc[r]);
        }
    }
    for (int r = 0; r < 40; r++) f_qkv[blockIdx.y][r * 4096 + col] = __float2bfloat16_rn(acc[r]);
}
__global__ void fb_attn() {
    __shared__ float p[40][41];
    const int hb = blockIdx.x * 128;
    for (int i = threadIdx.x; i < 1600; i += 128) {
        const int q = i / 40, k = i % 40; float a = 0.f;
        for (int e = 0; e < 128; e++) a = fmaf(__bfloat162float(f_qkv[0][q * 4096 + hb + e]), __bfloat162float(f_qkv[1][k * 4096 + hb + e]), a);
        p[q][k] = (q < 8 || q >= k) ? rbf(rbf(a) * 0.08838834764831845f) : -1.0e9f;
    }
    __syncthreads();
    if (threadIdx.x < 40) {
        float* r = p[threadIdx.x]; float mx = r[0], sum = 0.f;
        for (int k = 1; k < 40; k++) mx = fmaxf(mx, r[k]);
        for (int k = 0; k < 40; k++) { r[k] = expf(r[k] - mx); sum += r[k]; }
        for (int k = 0; k < 40; k++) r[k] = rbf(r[k] / sum);
    }
    __syncthreads();
    for (int q = 0; q < 40; q++) {
        float a = 0.f;
        for (int k = 0; k < 40; k++) a = fmaf(p[q][k], __bfloat162float(f_qkv[2][k * 4096 + hb + threadIdx.x]), a);
        f_o[q * 4096 + hb + threadIdx.x] = __float2bfloat16_rn(a);
    }
}
__global__ void fb_out(const AuxArgs P, bf16* memn, int s) {
    __shared__ float o[4096]; __shared__ float red[128];
    const int r = blockIdx.x, c = blockIdx.y * 128 + threadIdx.x;
    for (int i = threadIdx.x; i < 4096; i += 128) o[i] = __bfloat162float(f_o[r * 4096 + i]);
    const int row = s * 32 + r - 8;
    float ga = 0.f;
    if (r >= 8) for (int d = threadIdx.x; d < DM_; d += 128) ga += rbf(__bfloat162float(P.x[(size_t)row * DM_ + d]) * __bfloat162float(P.gatew[d]));
    red[threadIdx.x] = ga;
    __syncthreads();
    float a = 0.f;
    for (int k = 0; k < 4096; k++) a = fmaf(o[k], __bfloat162float(P.Wo[(size_t)k * DM_ + c]), a);
    if (r < 8) { memn[r * DM_ + c] = __float2bfloat16_rn(a); return; }
    ga = 0.f; for (int i = 0; i < 128; i++) ga += red[i];
    const float gt = rbf(1.f / (1.f + expf(-rbf(ga)))), og = rbf(1.f - gt);
    P.out[(size_t)row * DM_ + c] = __float2bfloat16_rn(rbf(gt * rbf(a)) + rbf(og * __bfloat162float(g_b[(size_t)row * DM_ + c])));
}

typedef CUresult (*EncodeFn)(CUtensorMap*, CUtensorMapDataType, cuuint32_t, void*, const cuuint64_t*, const cuuint64_t*,
                             const cuuint32_t*, const cuuint32_t*, CUtensorMapInterleave, CUtensorMapSwizzle,
                             CUtensorMapL2promotion, CUtensorMapFloatOOBfill);

extern "C" void kernel_launch(void* const* d_in, const int* in_sizes, int n_in, void* d_out, int out_size) {
    const bf16* x = (const bf16*)d_in[0];
    const bf16* mem0 = (const bf16*)d_in[1];
    const bf16* Wq = (const bf16*)d_in[2];
    const bf16* Wk = (const bf16*)d_in[3];
    const bf16* Wv = (const bf16*)d_in[4];
    const bf16* Wo = (const bf16*)d_in[5];
    const bf16* Bk = (const bf16*)d_in[8];
    const bf16* Bv = (const bf16*)d_in[9];
    const bf16* shk = (const bf16*)d_in[10];
    const bf16* ssmk = (const bf16*)d_in[11];
    const bf16* ssmD = (const bf16*)d_in[12];
    const bf16* gatew = (const bf16*)d_in[13];

    static EncodeFn enc = nullptr;
    static int fast = -1;
    if (fast < 0) {
        void* fn = nullptr; cudaDriverEntryPointQueryResult qr;
        cudaGetDriverEntryPoint("cuTensorMapEncodeTiled", &fn, cudaEnableDefault, &qr);
        enc = (EncodeFn)fn;
        cudaFuncSetAttribute(rec_kernel, cudaFuncAttributeMaxDynamicSharedMemorySize, A_SMEM + 1024);
        cudaFuncSetAttribute(rec_kernel, cudaFuncAttributeNonPortableClusterSizeAllowed, 1);
        cudaFuncSetAttribute(aux_kernel, cudaFuncAttributeMaxDynamicSharedMemorySize, B_SMEM);
        cudaLaunchConfig_t qc = {};
        qc.gridDim = dim3(A_CTAS); qc.blockDim = dim3(A_THREADS); qc.dynamicSmemBytes = A_SMEM + 1024;
        cudaLaunchAttribute qa[1];
        qa[0].id = cudaLaunchAttributeClusterDimension; qa[0].val.clusterDim.x = 16; qa[0].val.clusterDim.y = 1; qa[0].val.clusterDim.z = 1;
        qc.attrs = qa; qc.numAttrs = 1;
        int ncl = 0, nsm = 0, dev = 0;
        cudaGetDevice(&dev);
        cudaDeviceGetAttribute(&nsm, cudaDevAttrMultiProcessorCount, dev);
        if (cudaOccupancyMaxActiveClusters(&ncl, rec_kernel, &qc) != cudaSuccess) { ncl = 0; cudaGetLastError(); }
        fast = (enc != nullptr && ncl >= 7 && nsm >= A_CTAS + NB_CTAS - N_SPARE) ? 1 : 0;
    }
    if (!fast) {
        cudaStream_t fs = cudaStreamPerThread;
        AuxArgs FP = {x, Wo, Bk, Bv, shk, ssmk, ssmD, gatew, (bf16*)d_out};
        bf16* fm; cudaGetSymbolAddress((void**)&fm, f_mem);
        fb_conv<<<DM_, 256, 0, fs>>>(FP);
        for (int s = 0; s < NSEG_; s++) {
            fb_proj<<<dim3(32, 3), 128, 0, fs>>>(x, s == 0 ? mem0 : fm + (s & 1) * 8 * DM_, Wq, Wk, Wv, s);
            fb_attn<<<32, 128, 0, fs>>>();
            fb_out<<<dim3(40, 5), 128, 0, fs>>>(FP, fm + ((s + 1) & 1) * 8 * DM_, s);
        }
        return;
    }
    CUtensorMap tmx;
    {
        cuuint64_t dims[3] = {64, (cuuint64_t)S_, 10};
        cuuint64_t strides[2] = {DM_ * 2, 128};
        cuuint32_t box[3] = {64, 32, 1}, es[3] = {1, 1, 1};
        enc(&tmx, CU_TENSOR_MAP_DATA_TYPE_BFLOAT16, 3, (void*)x, dims, strides, box, es, CU_TENSOR_MAP_INTERLEAVE_NONE,
            CU_TENSOR_MAP_SWIZZLE_128B, CU_TENSOR_MAP_L2_PROMOTION_L2_256B, CU_TENSOR_MAP_FLOAT_OOB_FILL_NONE);
    }
    cudaStream_t st = cudaStreamPerThread;
    AuxArgs P = {x, Wo, Bk, Bv, shk, ssmk, ssmD, gatew, (bf16*)d_out};
    {
        cudaLaunchConfig_t ca = {};
        ca.gridDim = dim3(A_CTAS); ca.blockDim = dim3(A_THREADS); ca.dynamicSmemBytes = A_SMEM + 1024; ca.stream = st;
        cudaLaunchAttribute aa[1];
        aa[0].id = cudaLaunchAttributeClusterDimension; aa[0].val.clusterDim.x = 16; aa[0].val.clusterDim.y = 1; aa[0].val.clusterDim.z = 1;
        ca.attrs = aa; ca.numAttrs = 1;
        cudaLaunchKernelEx(&ca, rec_kernel, tmx, mem0, Wq, Wk, Wv, Wo, P);
    }
    cudaLaunchConfig_t cfg = {};
    cfg.gridDim = dim3(NB_CTAS - N_SPARE);
    cfg.blockDim = dim3(B_THREADS); cfg.dynamicSmemBytes = B_SMEM; cfg.stream = st;
    cudaLaunchAttribute at[1];
    at[0].id = cudaLaunchAttributeProgrammaticStreamSerialization; at[0].val.programmaticStreamSerializationAllowed = 1;
    cfg.attrs = at; cfg.numAttrs = 1;
    cudaLaunchKernelEx(&cfg, aux_kernel, P);
}
```

```cpp
#include <cuda_runtime.h>
#include <cuda_bf16.h>
#include <cuda.h>
#include <stdint.h>

typedef __nv_bfloat16 bf16;

constexpr int S_ = 2048, DM_ = 640, NH_ = 32, NSEG_ = 64;
constexpr int NKG_ = 7, NCR_ = 5, NB_CTAS = NKG_ * NCR_;

#define DELAY_X 200
#define LOOKW 20
#define START_DELAY 10000
#define SPIN_LIMIT (1 << 13)
#define SPIN_FAIL(guard, code) (((++guard) & 1023) == 0 && (guard >= SPIN_LIMIT || *(volatile unsigned*)&g_misc[2] != 0) && ((g_misc[2] = (code)), true))

__device__ uint2 g_X[4][40 * 7 * 32];
__device__ uint4 g_ox[(size_t)NSEG_ * NH_ * 512];
__device__ float g_part[(size_t)NKG_ * S_ * DM_];
__device__ bf16 g_b[(size_t)S_ * DM_];
__device__ float g_gate[S_];
__device__ unsigned g_oxcnt[NSEG_ * 8];
__device__ unsigned g_pcnt[NSEG_ * 8];
__device__ unsigned g_misc[4];
#define CAL(b, i) do {} while (0)

__device__ __forceinline__ uint32_t smem_u32(const void* p) { return (uint32_t)__cvta_generic_to_shared(p); }
__device__ __forceinline__ void mbar_init(uint32_t mb, int cnt) { asm volatile("mbarrier.init.shared.b64 [%0], %1;" ::"r"(mb), "r"(cnt)); }
__device__ __forceinline__ void mbar_expect(uint32_t mb, int bytes) { asm volatile("mbarrier.arrive.expect_tx.shared.b64 _, [%0], %1;" ::"r"(mb), "r"(bytes) : "memory"); }
__device__ __forceinline__ void mbar_arrive(uint32_t mb) { asm volatile("mbarrier.arrive.shared.b64 _, [%0];" ::"r"(mb) : "memory"); }
__device__ __forceinline__ bool mbar_try(uint32_t mb, int parity) {
    uint32_t ok;
    asm volatile("{ .reg .pred p; mbarrier.try_wait.parity.shared.b64 p, [%1], %2; selp.u32 %0, 1, 0, p; }" : "=r"(ok) : "r"(mb), "r"(parity) : "memory");
    return ok;
}
__device__ __forceinline__ void mbar_wait(uint32_t mb, int parity) {
    int guard = 0;
    while (!mbar_try(mb, parity)) { if (SPIN_FAIL(guard, 1)) break; }
}
__device__ __forceinline__ void mbar_wait_u(uint32_t mb, int parity) {
    asm volatile("{ .reg .pred p; .reg .u32 c; mov.u32 c, 0;\n"
                 "WL%=: mbarrier.try_wait.parity.shared.b64 p, [%0], %1;\n"
                 "@p bra.uni WD%=;\n"
                 "add.u32 c, c, 1; setp.lt.u32 p, c, 16384;\n"
                 "@p bra.uni WL%=;\n"
                 "WD%=: }" ::"r"(mb), "r"(parity) : "memory");
}
__device__ __forceinline__ uint32_t movm(uint32_t a) { uint32_t d; asm volatile("movmatrix.sync.aligned.m8n8.trans.b16 %0, %1;" : "=r"(d) : "r"(a)); return d; }
__device__ __forceinline__ float ex2(float x) { float y; asm("ex2.approx.ftz.f32 %0, %1;" : "=f"(y) : "f"(x)); return y; }
__device__ __forceinline__ float rcp(float x) { float y; asm("rcp.approx.ftz.f32 %0, %1;" : "=f"(y) : "f"(x)); return y; }
__device__ __forceinline__ uint32_t mapa(uint32_t a, uint32_t r) { uint32_t o; asm volatile("mapa.shared::cluster.u32 %0, %1, %2;" : "=r"(o) : "r"(a), "r"(r)); return o; }
__device__ __forceinline__ uint4 ld_poll16(const void* p) { uint4 v; asm volatile("ld.relaxed.gpu.global.v4.u32 {%0,%1,%2,%3}, [%4];" : "=r"(v.x), "=r"(v.y), "=r"(v.z), "=r"(v.w) : "l"(p) : "memory"); return v; }
__device__ __forceinline__ void st_rel16(void* p, uint4 v) { asm volatile("st.relaxed.gpu.global.v4.u32 [%0], {%1,%2,%3,%4};" ::"l"(p), "r"(v.x), "r"(v.y), "r"(v.z), "r"(v.w) : "memory"); }
__device__ __forceinline__ void st_rel4(void* p, uint32_t v) { asm volatile("st.relaxed.gpu.global.u32 [%0], %1;" ::"l"(p), "r"(v) : "memory"); }
__device__ __forceinline__ unsigned ld_acq(const unsigned* p) { unsigned v; asm volatile("ld.acquire.gpu.global.u32 %0, [%1];" : "=r"(v) : "l"(p) : "memory"); return v; }
__device__ __forceinline__ void red_rel(unsigned* p, unsigned v) { asm volatile("red.release.gpu.global.add.u32 [%0], %1;" ::"l"(p), "r"(v) : "memory"); }
__device__ __forceinline__ void bar_sync(int id, int n) { asm volatile("bar.sync %0, %1;" ::"r"(id), "r"(n) : "memory"); }
__device__ __forceinline__ void st_async8(uint32_t dst, uint32_t a, uint32_t b, uint32_t mb) {
    asm volatile("st.async.weak.shared::cluster.mbarrier::complete_tx::bytes.v2.b32 [%0], {%1,%2}, [%3];" ::"r"(dst), "r"(a), "r"(b), "r"(mb) : "memory");
}
__device__ __forceinline__ void st_async16(uint32_t dst, uint32_t a, uint32_t b, uint32_t c, uint32_t d, uint32_t mb) {
    asm volatile("st.async.weak.shared::cluster.mbarrier::complete_tx::bytes.v4.b32 [%0], {%1,%2,%3,%4}, [%5];" ::"r"(dst), "r"(a), "r"(b), "r"(c), "r"(d), "r"(mb) : "memory");
}
__device__ __forceinline__ uint2 lds64(uint32_t a) { uint2 v; asm volatile("ld.shared.v2.u32 {%0,%1}, [%2];" : "=r"(v.x), "=r"(v.y) : "r"(a) : "memory"); return v; }
__device__ __forceinline__ uint2 ld_poll8(const void* p) { uint2 v; asm volatile("ld.relaxed.gpu.global.v2.u32 {%0,%1}, [%2];" : "=r"(v.x), "=r"(v.y) : "l"(p) : "memory"); return v; }
__device__ __forceinline__ void bulk_s2s(uint32_t dst, uint32_t src, uint32_t bytes, uint32_t mb) {
    asm volatile("cp.async.bulk.shared::cluster.shared::cta.mbarrier::complete_tx::bytes [%0], [%1], %2, [%3];" ::"r"(dst), "r"(src), "r"(bytes), "r"(mb) : "memory");
}
__device__ __forceinline__ void bulk_g2s(uint32_t dst, const void* src, uint32_t bytes, uint32_t mb) {
    asm volatile("cp.async.bulk.shared::cluster.global.mbarrier::complete_tx::bytes [%0], [%1], %2, [%3];" ::"r"(dst), "l"(src), "r"(bytes), "r"(mb) : "memory");
}
__device__ __forceinline__ void tma3d(uint32_t dst, const CUtensorMap* tm, int c0, int c1, int c2, uint32_t mb) {
    asm volatile("cp.async.bulk.tensor.3d.shared::cluster.global.mbarrier::complete_tx::bytes [%0], [%1, {%3, %4, %5}], [%2];"
                 ::"r"(dst), "l"((uint64_t)tm), "r"(mb), "r"(c0), "r"(c1), "r"(c2) : "memory");
}
__device__ __forceinline__ void tma3d_mc(uint32_t dst, const CUtensorMap* tm, int c0, int c1, int c2, uint32_t mb, uint16_t mask) {
    asm volatile("cp.async.bulk.tensor.3d.shared::cluster.global.mbarrier::complete_tx::bytes.multicast::cluster [%0], [%1, {%3, %4, %5}], [%2], %6;"
                 ::"r"(dst), "l"((uint64_t)tm), "r"(mb), "r"(c0), "r"(c1), "r"(c2), "h"(mask) : "memory");
}
__device__ __forceinline__ void st_rel8(void* p, uint32_t a, uint32_t b) { asm volatile("st.relaxed.gpu.global.v2.u32 [%0], {%1,%2};" ::"l"(p), "r"(a), "r"(b) : "memory"); }
__device__ __forceinline__ void fence_async_smem() { asm volatile("fence.proxy.async.shared::cta;" ::: "memory"); }
__device__ __forceinline__ void fence_async_all() { asm volatile("fence.proxy.async;" ::: "memory"); }
__device__ __forceinline__ void cp_async16(uint32_t dst, const void* src) { asm volatile("cp.async.cg.shared.global [%0], [%1], 16;" ::"r"(dst), "l"(src) : "memory"); }
__device__ __forceinline__ void cluster_sync() { asm volatile("barrier.cluster.arrive.aligned; barrier.cluster.wait.aligned;" ::: "memory"); }
__device__ __forceinline__ int clk() { int c; asm volatile("mov.u32 %0, %%clock;" : "=r"(c)); return c; }

__device__ __forceinline__ void ldsm4(uint32_t* r, uint32_t a) { asm volatile("ldmatrix.sync.aligned.m8n8.x4.shared.b16 {%0,%1,%2,%3}, [%4];" : "=r"(r[0]), "=r"(r[1]), "=r"(r[2]), "=r"(r[3]) : "r"(a) : "memory"); }
__device__ __forceinline__ void ldsm2(uint32_t* r, uint32_t a) { asm volatile("ldmatrix.sync.aligned.m8n8.x2.shared.b16 {%0,%1}, [%2];" : "=r"(r[0]), "=r"(r[1]) : "r"(a) : "memory"); }
__device__ __forceinline__ void ldsm4t(uint32_t* r, uint32_t a) { asm volatile("ldmatrix.sync.aligned.m8n8.x4.trans.shared.b16 {%0,%1,%2,%3}, [%4];" : "=r"(r[0]), "=r"(r[1]), "=r"(r[2]), "=r"(r[3]) : "r"(a) : "memory"); }
__device__ __forceinline__ void ldsm2t(uint32_t* r, uint32_t a) { asm volatile("ldmatrix.sync.aligned.m8n8.x2.trans.shared.b16 {%0,%1}, [%2];" : "=r"(r[0]), "=r"(r[1]) : "r"(a) : "memory"); }
__device__ __forceinline__ void stsm4t(uint32_t a, uint32_t r0, uint32_t r1, uint32_t r2, uint32_t r3) {
    asm volatile("stmatrix.sync.aligned.m8n8.x4.trans.shared.b16 [%0], {%1,%2,%3,%4};" ::"r"(a), "r"(r0), "r"(r1), "r"(r2), "r"(r3) : "memory");
}
__device__ __forceinline__ uint4 lds128(uint32_t a) { uint4 v; asm volatile("ld.shared.v4.u32 {%0,%1,%2,%3}, [%4];" : "=r"(v.x), "=r"(v.y), "=r"(v.z), "=r"(v.w) : "r"(a) : "memory"); return v; }
__device__ __forceinline__ float2 lds64f(uint32_t a) { float2 v; asm volatile("ld.shared.v2.f32 {%0,%1}, [%2];" : "=f"(v.x), "=f"(v.y) : "r"(a) : "memory"); return v; }
__device__ __forceinline__ float lds32f(uint32_t a) { float v; asm volatile("ld.shared.f32 %0, [%1];" : "=f"(v) : "r"(a) : "memory"); return v; }
__device__ __forceinline__ uint32_t lds32(uint32_t a) { uint32_t v; asm volatile("ld.shared.u32 %0, [%1];" : "=r"(v) : "r"(a) : "memory"); return v; }
__device__ __forceinline__ void sts128(uint32_t a, uint4 v) { asm volatile("st.shared.v4.u32 [%0], {%1,%2,%3,%4};" ::"r"(a), "r"(v.x), "r"(v.y), "r"(v.z), "r"(v.w) : "memory"); }
__device__ __forceinline__ void sts128f(uint32_t a, float x, float y, float z, float w) { asm volatile("st.shared.v4.f32 [%0], {%1,%2,%3,%4};" ::"r"(a), "f"(x), "f"(y), "f"(z), "f"(w) : "memory"); }
__device__ __forceinline__ void sts64f(uint32_t a, float x, float y) { asm volatile("st.shared.v2.f32 [%0], {%1,%2};" ::"r"(a), "f"(x), "f"(y) : "memory"); }
__device__ __forceinline__ void sts64(uint32_t a, uint32_t x, uint32_t y) { asm volatile("st.shared.v2.u32 [%0], {%1,%2};" ::"r"(a), "r"(x), "r"(y) : "memory"); }
__device__ __forceinline__ void sts32f(uint32_t a, float x) { asm volatile("st.shared.f32 [%0], %1;" ::"r"(a), "f"(x) : "memory"); }

__device__ __forceinline__ void mma16(float* d, const uint32_t* a, uint32_t b0, uint32_t b1) {
    asm volatile("mma.sync.aligned.m16n8k16.row.col.f32.bf16.bf16.f32 {%0,%1,%2,%3}, {%4,%5,%6,%7}, {%8,%9}, {%0,%1,%2,%3};"
                 : "+f"(d[0]), "+f"(d[1]), "+f"(d[2]), "+f"(d[3]) : "r"(a[0]), "r"(a[1]), "r"(a[2]), "r"(a[3]), "r"(b0), "r"(b1));
}
__device__ __forceinline__ void mma16r(float* d, uint32_t a0, uint32_t a1, uint32_t a2, uint32_t a3, uint32_t b0, uint32_t b1) {
    asm volatile("mma.sync.aligned.m16n8k16.row.col.f32.bf16.bf16.f32 {%0,%1,%2,%3}, {%4,%5,%6,%7}, {%8,%9}, {%0,%1,%2,%3};"
                 : "+f"(d[0]), "+f"(d[1]), "+f"(d[2]), "+f"(d[3]) : "r"(a0), "r"(a1), "r"(a2), "r"(a3), "r"(b0), "r"(b1));
}
__device__ __forceinline__ void mma8(float* d, uint32_t a0, uint32_t a1, uint32_t b0) {
    asm volatile("mma.sync.aligned.m16n8k8.row.col.f32.bf16.bf16.f32 {%0,%1,%2,%3}, {%4,%5}, {%6}, {%0,%1,%2,%3};"
                 : "+f"(d[0]), "+f"(d[1]), "+f"(d[2]), "+f"(d[3]) : "r"(a0), "r"(a1), "r"(b0));
}
__device__ __forceinline__ void wgmma_n32(float* d, const uint32_t* a, uint32_t desc_lo, int sc) {
    asm volatile("{ .reg .pred p; .reg .b64 dd; setp.ne.b32 p, %21, 0; mov.b64 dd, {%20, 0x40000040};\n"
                 "wgmma.mma_async.sync.aligned.m64n32k16.f32.bf16.bf16 {%0,%1,%2,%3,%4,%5,%6,%7,%8,%9,%10,%11,%12,%13,%14,%15}, {%16,%17,%18,%19}, dd, p, 1, 1, 0; }\n"
                 : "+f"(d[0]), "+f"(d[1]), "+f"(d[2]), "+f"(d[3]), "+f"(d[4]), "+f"(d[5]), "+f"(d[6]), "+f"(d[7]),
                   "+f"(d[8]), "+f"(d[9]), "+f"(d[10]), "+f"(d[11]), "+f"(d[12]), "+f"(d[13]), "+f"(d[14]), "+f"(d[15])
                 : "r"(a[0]), "r"(a[1]), "r"(a[2]), "r"(a[3]), "r"(desc_lo), "r"(sc));
}
#define WG_FENCE() asm volatile("wgmma.fence.sync.aligned;" ::: "memory")
#define WG_COMMIT() asm volatile("wgmma.commit_group.sync.aligned;" ::: "memory")
#define WG_WAIT0() asm volatile("wgmma.wait_group.sync.aligned 0;" ::: "memory")
__device__ __forceinline__ uint32_t desc_sw128(uint32_t saddr) { return ((saddr & 0x3FFFF) >> 4) | (1u << 16); }
__device__ __forceinline__ uint32_t pack2(float lo, float hi) { __nv_bfloat162 h = __floats2bfloat162_rn(lo, hi); return *(uint32_t*)&h; }
__device__ __forceinline__ float bflo(uint32_t u) { return __uint_as_float(u << 16); }
__device__ __forceinline__ float bfhi(uint32_t u) { return __uint_as_float(u & 0xffff0000u); }
__device__ __forceinline__ float rbf(float x) { return __uint_as_float(pack2(0.f, x)); }
__device__ __forceinline__ uint32_t nzw(uint32_t u) { return u == 0 ? 0x80008000u : u; }
__device__ __forceinline__ uint32_t min4(uint4 v) { return min(min(v.x, v.y), min(v.z, v.w)); }
__device__ __forceinline__ void mbar_arrive_if(uint32_t mb, uint32_t c) {
    asm volatile("{ .reg .pred p; setp.ne.u32 p, %1, 0; @p mbarrier.arrive.shared.b64 _, [%0]; }" ::"r"(mb), "r"(c) : "memory");
}
__device__ __forceinline__ int eperm(int p) { return (p & ~15) + 2 * (p & 7) + ((p >> 3) & 1); }

constexpr int U_STRIDE = 136 * 48;
constexpr int KR_STRIDE = 2080 * 2 * 2;
constexpr int B_U_OFF = 0, B_KR_OFF = 8 * U_STRIDE, B_CONV_END = B_KR_OFF + 8 * KR_STRIDE;
constexpr int B_OX_STAGES = 3, B_OX_BYTES = 40960;
constexpr int B_BAR_OFF = B_OX_STAGES * B_OX_BYTES;
constexpr int B_SMEM = B_BAR_OFF + 128;

constexpr int B_THREADS = 384;
constexpr int B_LAG = 2;

struct AuxArgs { const bf16 *x, *Wo, *Bk, *Bv, *shk, *ssmk, *ssmD, *gatew; bf16* out; };
constexpr int MBB_FULL = B_BAR_OFF, MBB_EMPTY = B_BAR_OFF + 24, MBB_ST = B_BAR_OFF + 48, MBB_GO = B_BAR_OFF + 80, MBB_FLAG = B_BAR_OFF + 96;

__device__ __forceinline__ void aux_init(uint32_t sb) {
    for (int i = 0; i < B_OX_STAGES; i++) { mbar_init(sb + MBB_FULL + 8 * i, 1); mbar_init(sb + MBB_EMPTY + 8 * i, 8); }
    for (int i = 0; i < 4; i++) mbar_init(sb + MBB_ST + 8 * i, 8);
    mbar_init(sb + MBB_GO, 8);
    fence_async_smem();
}
__device__ __forceinline__ bool mbar_test(uint32_t mb, int parity) {
    uint32_t ok;
    asm volatile("{ .reg .pred p; mbarrier.test_wait.parity.shared.b64 p, [%1], %2; selp.u32 %0, 1, 0, p; }" : "=r"(ok) : "r"(mb), "r"(parity) : "memory");
    return ok;
}
__device__ __forceinline__ bool aux_quiet(int p) { return p >= 4 && p < 16 && ((p - 4) & 2) == 0; }
__device__ __forceinline__ int aux_ord(int p) { return p < 4 ? p : (p < 16 ? 4 + ((p - 4) >> 2) * 2 + (p & 1) : p - 6); }
__device__ __forceinline__ int aux_vid(int p) {
    if (aux_quiet(p)) { const int qi = ((p - 4) >> 2) * 2 + (p & 1); return qi < 5 ? 30 + qi : 25; }
    const int o = aux_ord(p); return o < 25 ? o : o + 1;
}
constexpr unsigned AUX_EXITS = NB_CTAS + 29 * 3 + 1;
__device__ __forceinline__ bool aux_exit_last() {
    unsigned old; asm volatile("atom.acq_rel.gpu.global.add.u32 %0, [%1], 1;" : "=r"(old) : "l"(&g_misc[1]) : "memory");
    return old == AUX_EXITS - 1;
}
__device__ __forceinline__ void aux_reset(int i0, int step) {
    for (int i = i0; i < NSEG_ * 8; i += step) { g_oxcnt[i] = 0; g_pcnt[i] = 0; }
    if (i0 == 0) { g_misc[0] = 0; g_misc[1] = 0; }
}
__device__ __forceinline__ void aux_final(const AuxArgs& P, int p, int fw) {
    const int vid = aux_vid(p), kg = vid / NCR_, cr = vid % NCR_, nf = cr == 0 ? 5 : 6;
    const int lane = threadIdx.x & 31, c = cr * 128 + lane * 4;
    const int r0 = vid == 25 ? 30 : kg + nf * fw, rstep = vid == 25 ? 1 : 3 * nf, rend = (cr == 0 && vid != 25) ? 30 : 32;
    if (lane == 0) { int guard = 0; while (ld_acq(&g_misc[0]) < (unsigned)(NB_CTAS + 1)) { if (++guard > (1 << 20)) break; __nanosleep(500); } }
    __syncwarp();
    int ready = 0;
#pragma unroll 1
    for (int n = 0; n < NSEG_; n++) {
        if (n >= ready) {
            int guard = 0;
            while (true) {
                const bool ok = n + lane < NSEG_ && ld_acq(&g_pcnt[(n + lane) * 8 + cr]) >= (unsigned)NKG_;
                const unsigned m = __ballot_sync(~0u, ok);
                ready = n + (m == ~0u ? 32 : __ffs(~m) - 1);
                if (ready > n) break;
                if (++guard > (1 << 18)) { g_misc[2] = 6; ready = NSEG_; break; }
                __nanosleep(100);
            }
            __syncwarp();
        }
#pragma unroll 1
        for (int r = r0; r < rend; r += rstep) {
            const int row = n * 32 + r;
            float4 v[NKG_];
#pragma unroll
            for (int k = 0; k < NKG_; k++) v[k] = __ldcg((const float4*)(g_part + ((size_t)k * S_ + row) * DM_ + c));
            const float gt = __ldcg(&g_gate[row]), og = rbf(1.f - gt);
            const uint2 bv = __ldcg((const uint2*)(g_b + (size_t)row * DM_ + c));
            float4 a = v[0];
#pragma unroll
            for (int k = 1; k < NKG_; k++) { a.x += v[k].x; a.y += v[k].y; a.z += v[k].z; a.w += v[k].w; }
            uint2 o;
            o.x = pack2(rbf(gt * rbf(a.x)) + rbf(og * bflo(bv.x)), rbf(gt * rbf(a.y)) + rbf(og * bfhi(bv.x)));
            o.y = pack2(rbf(gt * rbf(a.z)) + rbf(og * bflo(bv.y)), rbf(gt * rbf(a.w)) + rbf(og * bfhi(bv.y)));
            *(uint2*)(P.out + (size_t)row * DM_ + c) = o;
        }
    }
    bool last = false;
    if (lane == 0) last = aux_exit_last();
    if (__shfl_sync(~0u, last, 0)) aux_reset(lane, 32);
}
__device__ __forceinline__ void aux_control(uint32_t sb, int p) {
    const int vid = aux_vid(p), kg = vid / NCR_, cr = vid % NCR_;
    const int h0 = kg < 4 ? kg * 5 : 20 + (kg - 4) * 4, nh = kg < 4 ? 5 : 4;
    { int guard = 0; while (!mbar_try(sb + MBB_GO, 0)) { if (++guard > (1 << 22)) break; } }
    red_rel(&g_misc[0], 1);
    if (p == NB_CTAS) return;
    int nl = 0, nr = 0, guard = 0;
    while (nr < NSEG_) {
        bool did = false;
        if (nl < NSEG_ && nl < nr + 4) {
            const int st = nl % B_OX_STAGES;
            if ((nl < B_OX_STAGES || mbar_test(sb + MBB_EMPTY + 8 * st, (nl / B_OX_STAGES - 1) & 1)) &&
                ld_acq(&g_oxcnt[nl * 8 + kg]) >= (unsigned)(2 * nh)) {
                fence_async_all();
                mbar_expect(sb + MBB_FULL + 8 * st, nh * 8192);
                bulk_g2s(sb + st * B_OX_BYTES, g_ox + (size_t)(nl * NH_ + h0) * 512, nh * 8192, sb + MBB_FULL + 8 * st);
                nl++; did = true;
            }
        }
        if (nr < nl && mbar_test(sb + MBB_ST + 8 * (nr & 3), (nr >> 2) & 1)) { red_rel(&g_pcnt[nr * 8 + cr], 1); nr++; did = true; }
        if (did) guard = 0;
        else { if (++guard > (1 << 17)) { g_misc[2] = 4; break; } __nanosleep(100); }
    }
    if (aux_exit_last()) aux_reset(0, 1);
}
__device__ __forceinline__ void aux_compute(const AuxArgs& P, unsigned char* smem, uint32_t sb, int cta, int warp) {
    const bf16* __restrict__ x = P.x; const bf16* __restrict__ Wo = P.Wo; const bf16* __restrict__ Bk = P.Bk; const bf16* __restrict__ Bv = P.Bv;
    const bf16* __restrict__ shk = P.shk; const bf16* __restrict__ ssmk = P.ssmk; const bf16* __restrict__ ssmD = P.ssmD;
    const bf16* __restrict__ gatew = P.gatew; bf16* __restrict__ out = P.out;
    const int tid = threadIdx.x, lane = tid & 31;
    const int g = lane >> 2, t = lane & 3;
    const int vid = aux_vid(cta), kg = vid / NCR_, cr = vid % NCR_;
    const bool quiet = aux_quiet(cta);
    const int ord = aux_ord(cta);
    const int h0 = kg < 4 ? kg * 5 : 20 + (kg - 4) * 4, nh = kg < 4 ? 5 : 4;
    const uint32_t mb_full = sb + MBB_FULL, mb_empty = sb + MBB_EMPTY, mb_st = sb + MBB_ST, mb_go = sb + MBB_GO;
    CAL(112 + cta, 0);
    if (cta == NB_CTAS) { const long long t0 = clock64(); while (clock64() - t0 < START_DELAY) __nanosleep(200); }
    else if (!quiet) {
        { const long long t0 = clock64(); while (clock64() - t0 < START_DELAY) __nanosleep(200); }
        uint32_t wv[10];
#pragma unroll
        for (int i = 0; i < 10; i++) wv[i] = __ldg((const uint32_t*)gatew + lane + 32 * i);
        uint32_t xv[9][10];
#pragma unroll
        for (int j = 0; j < 9; j++) {
            const int r = min(ord * 8 + warp + j * 232, S_ - 1);
#pragma unroll
            for (int i = 0; i < 10; i++) xv[j][i] = __ldg((const uint32_t*)(x + (size_t)r * DM_) + lane + 32 * i);
        }
#pragma unroll
        for (int j = 0; j < 9; j++) {
            const int r = ord * 8 + warp + j * 232;
            float acc = 0.f;
#pragma unroll
            for (int i = 0; i < 10; i++) acc += rbf(bflo(xv[j][i]) * bflo(wv[i])) + rbf(bfhi(xv[j][i]) * bfhi(wv[i]));
#pragma unroll
            for (int o = 16; o; o >>= 1) acc += __shfl_xor_sync(~0u, acc, o);
            if (lane == 0 && r < S_) g_gate[r] = rbf(1.f / (1.f + __expf(-rbf(acc))));
        }
    }

    int item0, nitem;
    if (cta >= 16) { item0 = 3 * (cta - 16); nitem = 3; }
    else { item0 = 60 + 2 * ord; nitem = quiet ? 0 : 2; }
    for (int item = item0; item < item0 + nitem; item++) {
        const int c0 = item * 8;
        bar_sync(1, 256);
        for (int i = tid; i < 8 * 24; i += 256) sts128(sb + B_U_OFF + (i / 24) * U_STRIDE + (i % 24) * 16, make_uint4(0, 0, 0, 0));
        {
            const uint32_t krb = sb + B_KR_OFF + warp * KR_STRIDE;
            const bf16* kp = ssmk + (size_t)(c0 + warp) * S_;
            uint4 v[8]; uint32_t pv[8];
#pragma unroll
            for (int j = 0; j < 8; j++) {
                const int i = lane + 32 * j;
                v[j] = __ldg((const uint4*)kp + i);
                pv[j] = i > 0 ? __ldg((const uint32_t*)kp + 4 * i - 1) : 0u;
            }
#pragma unroll
            for (int j = 0; j < 8; j++) {
                const int i = lane + 32 * j;
                sts128(krb + (2040 - 8 * i) * 2, make_uint4(__byte_perm(v[j].w, 0, 0x1032), __byte_perm(v[j].z, 0, 0x1032),
                                                            __byte_perm(v[j].y, 0, 0x1032), __byte_perm(v[j].x, 0, 0x1032)));
                sts128(krb + 4160 + (2040 - 8 * i) * 2, make_uint4(__byte_perm(v[j].w, v[j].z, 0x7610), __byte_perm(v[j].z, v[j].y, 0x7610),
                                                                   __byte_perm(v[j].y, v[j].x, 0x7610), __byte_perm(v[j].x, pv[j], 0x7610)));
            }
            if (lane < 4) { sts128(krb + 4096 + lane * 16, make_uint4(0, 0, 0, 0)); sts128(krb + 4160 + 4096 + lane * 16, make_uint4(0, 0, 0, 0)); }
        }
        {
            float sh[8][4];
#pragma unroll
            for (int c = 0; c < 8; c++) {
                uint2 v = __ldg((const uint2*)(shk + (c0 + c) * 4));
                sh[c][0] = bflo(v.x); sh[c][1] = bfhi(v.x); sh[c][2] = bflo(v.y); sh[c][3] = bfhi(v.y);
            }
            const int t0 = tid * 8;
            uint4 kr[11], vr[8];
#pragma unroll
            for (int i = 0; i < 11; i++) { int r = t0 - 3 + i; kr[i] = r >= 0 ? __ldg((const uint4*)(Bk + (size_t)r * DM_ + c0)) : make_uint4(0, 0, 0, 0); }
#pragma unroll
            for (int i = 0; i < 8; i++) vr[i] = __ldg((const uint4*)(Bv + (size_t)(t0 + i) * DM_ + c0));
#pragma unroll
            for (int c = 0; c < 8; c++) {
                float res[8];
#pragma unroll
                for (int i = 0; i < 8; i++) {
                    float a = 0.f;
#pragma unroll
                    for (int tt = 0; tt < 4; tt++) {
                        uint32_t wd = ((const uint32_t*)&kr[i + tt])[c >> 1];
                        float kv_ = (c & 1) ? bfhi(wd) : bflo(wd);
                        a = rbf(a + rbf(kv_ * sh[c][3 - tt]));
                    }
                    uint32_t wd = ((const uint32_t*)&vr[i])[c >> 1];
                    res[i] = a * ((c & 1) ? bfhi(wd) : bflo(wd));
                }
                uint4 o = make_uint4(pack2(res[0], res[1]), pack2(res[2], res[3]), pack2(res[4], res[5]), pack2(res[6], res[7]));
                sts128(sb + B_U_OFF + c * U_STRIDE + (8 + (tid >> 1)) * 48 + (tid & 1) * 16, o);
            }
        }
        bar_sync(1, 256);
        {
            float acc[16][4];
#pragma unroll
            for (int i = 0; i < 64; i++) ((float*)acc)[i] = 0.f;
            const uint32_t kb = sb + B_KR_OFF + warp * KR_STRIDE + ((g & 1) ? (2047 - g + 2 * t) * 2 : 4160 + (2046 - g + 2 * t) * 2);
            const uint32_t ub = sb + B_U_OFF + warp * U_STRIDE + (8 + (lane & 7) + (lane >> 4) * 8) * 48 + ((lane >> 3) & 1) * 16;
#pragma unroll 1
            for (int r = 0; r < 8; r++) {
                uint32_t pa[16][3];
#pragma unroll
                for (int m = 0; m < 16; m++) {
                    const uint32_t a = kb - (16 * (r + 8 * m)) * 2;
                    pa[m][0] = lds32(a + 16); pa[m][1] = lds32(a); pa[m][2] = lds32(a - 16);
                }
#pragma unroll
                for (int d = 0; d < 16; d += 2) {
                    uint32_t b[4];
                    ldsm4(b, ub + (8 * d - r) * 48);
#pragma unroll
                    for (int m = 0; m < 16 - d; m++) mma16r(acc[m + d], pa[m][1], pa[m][2], pa[m][0], pa[m][1], b[0], b[1]);
#pragma unroll
                    for (int m = 0; m < 15 - d; m++) mma16r(acc[m + d + 1], pa[m][1], pa[m][2], pa[m][0], pa[m][1], b[2], b[3]);
                }
            }
            __syncwarp();
            const float Dv = __bfloat162float(ssmD[c0 + warp]);
            bf16* u = (bf16*)(smem + B_U_OFF + warp * U_STRIDE) + 8 * 24;
#pragma unroll
            for (int i = 0; i < 16; i++) {
#pragma unroll
                for (int q = 0; q < 4; q++) {
                    const int idx = (8 * i + 2 * t + (q & 1)) * 24 + g + (q >> 1) * 8;
                    const float kvv = __bfloat162float(u[idx]);
                    u[idx] = __float2bfloat16_rn(rbf(acc[i][q]) + rbf(kvv * Dv));
                }
            }
        }
        uint4 xv[8];
#pragma unroll
        for (int j = 0; j < 8; j++) xv[j] = __ldg((const uint4*)(x + (size_t)(tid + 256 * j) * DM_ + c0));
        bar_sync(1, 256);
#pragma unroll
        for (int j = 0; j < 8; j++) {
            const int r = tid + 256 * j;
            uint32_t o[4];
            const bf16* u = (const bf16*)(smem + B_U_OFF) + (8 + (r >> 4)) * 24 + (r & 15);
#pragma unroll
            for (int c = 0; c < 4; c++) {
                uint32_t wd = ((const uint32_t*)&xv[j])[c];
                o[c] = pack2(bflo(wd) * __bfloat162float(u[(2 * c) * (U_STRIDE / 2)]), bfhi(wd) * __bfloat162float(u[(2 * c + 1) * (U_STRIDE / 2)]));
            }
            *(uint4*)(g_b + (size_t)r * DM_ + c0) = make_uint4(o[0], o[1], o[2], o[3]);
        }
    }
    fence_async_smem();
    __syncwarp();
    if (lane == 0) mbar_arrive(mb_go);
    CAL(112 + cta, 1);
    if (cta == NB_CTAS) return;

    const int wg = warp >> 2, w = warp & 3;
    const int col = cr * 128 + wg * 64 + 16 * w + 2 * g;
    uint32_t A[40][4];
#pragma unroll
    for (int ks = 0; ks < 40; ks++) {
        const int hh = ks >> 3;
        uint32_t r[4] = {0, 0, 0, 0};
        if (hh < nh) {
#pragma unroll
            for (int i = 0; i < 4; i++) {
                const int p = (ks & 7) * 16 + 2 * t + (i & 1) + (i >> 1) * 8;
                r[i] = __ldg((const uint32_t*)(Wo + (size_t)((h0 + hh) * 128 + eperm(p)) * DM_ + col));
            }
        }
        A[ks][0] = __byte_perm(r[0], r[1], 0x5410); A[ks][1] = __byte_perm(r[0], r[1], 0x7632);
        A[ks][2] = __byte_perm(r[2], r[3], 0x5410); A[ks][3] = __byte_perm(r[2], r[3], 0x7632);
    }
    CAL(112 + cta, 2);
#pragma unroll 1
    for (int n = 0; n < NSEG_; n++) {
        const int st = n % B_OX_STAGES;
        { int guard = 0; while (!mbar_try(mb_full + 8 * st, (n / B_OX_STAGES) & 1)) { if (++guard > (1 << 20)) break; } }
        __syncwarp();
        float acc[16];
        const uint32_t d0 = __shfl_sync(0xffffffffu, desc_sw128(sb + st * B_OX_BYTES), 0);
        WG_FENCE();
#pragma unroll
        for (int ks = 0; ks < 32; ks++) wgmma_n32(acc, A[ks], d0 + (((ks >> 2) * 4096 + (ks & 3) * 32) >> 4), ks > 0);
        if (nh == 5) {
#pragma unroll
            for (int ks = 32; ks < 40; ks++) wgmma_n32(acc, A[ks], d0 + (((ks >> 2) * 4096 + (ks & 3) * 32) >> 4), 1);
        }
        WG_COMMIT();
        WG_WAIT0();
        if (lane == 0) mbar_arrive(mb_empty + 8 * st);
        float* pp = g_part + ((size_t)kg * S_ + n * 32) * DM_ + col;
#pragma unroll
        for (int j = 0; j < 4; j++) {
            *(float2*)(pp + (size_t)(8 * j + 2 * t) * DM_) = make_float2(acc[4 * j], acc[4 * j + 2]);
            *(float2*)(pp + (size_t)(8 * j + 2 * t + 1) * DM_) = make_float2(acc[4 * j + 1], acc[4 * j + 3]);
        }
        __syncwarp();
        if (lane == 0) mbar_arrive(mb_st + 8 * (n & 3));
    }
    CAL(112 + cta, 3);
}

constexpr int N_SPARE = 16;
__global__ void __launch_bounds__(B_THREADS, 1) aux_kernel(const AuxArgs P) {
    extern __shared__ __align__(1024) unsigned char smem[];
    const uint32_t sb = __shfl_sync(0xffffffffu, smem_u32(smem), 0);
    const int warp = __shfl_sync(0xffffffffu, threadIdx.x >> 5, 0);
    const int cta = N_SPARE + blockIdx.x;
    if (threadIdx.x == 0) aux_init(sb);
    __syncthreads();
    if (warp >= 8) {
        asm volatile("setmaxnreg.dec.sync.aligned.u32 56;");
        if (warp == 11) { if (threadIdx.x == 352) aux_control(sb, cta); }
        else if (cta < NB_CTAS) aux_final(P, cta, warp - 8);
    } else {
        asm volatile("setmaxnreg.inc.sync.aligned.u32 224;");
        aux_compute(P, smem, sb, cta, warp);
    }
}

constexpr int XT_OFF = 0, WO_OFF = 81920, WO_STRIDE = 464, KV_STRIDE = 272, XB_BYTES = 32 * KV_STRIDE, QX_BYTES = 16 * KV_STRIDE,
              K_OFF = 141312, V_OFF = K_OFF + 2 * XB_BYTES, EX_OFF = V_OFF + 2 * XB_BYTES  ,
              QX_OFF = EX_OFF + XB_BYTES, QF_OFF = QX_OFF + 2 * QX_BYTES, KF_OFF = QF_OFF + 2048, VF_OFF = KF_OFF + 4096,
              IN_OFF = VF_OFF + 4096, M_OFF = IN_OFF + 3840, EX2_OFF = M_OFF + 10240 + 512  ,
              BAR_OFF = EX2_OFF + XB_BYTES, A_SMEM = BAR_OFF + 144;
constexpr int O_OFF = QF_OFF;
__device__ __forceinline__ uint32_t kv_off(int which, int role, int n) {
    const int base = which == 1 ? K_OFF : V_OFF;
    if (which != role) return base + (n & 1) * XB_BYTES;
    const int j = n % 3;
    return j == 2 ? EX_OFF : base + j * XB_BYTES;
}
__device__ __forceinline__ void tile_owner(int r, int tau, int nown, int& gr, int& rk) {
    const int q = tau < 8 ? 16 + 8 * r + tau : 6 * r + tau - 8;
    gr = q >= 2 * nown ? 2 : (q >= nown ? 1 : 0);
    rk = q - gr * nown;
    if (q >= 3 * nown) { rk = 12 + ((q - 36) >> 1); gr = (q - 36) & 1; }
}
__device__ __forceinline__ int slot_tile(int q) { return q < 16 ? 14 * (q / 6) + 8 + q % 6 : 14 * ((q - 16) >> 3) + ((q - 16) & 7); }
__host__ __device__ constexpr int korder(int i) { return i < 24 ? 14 * (i >> 3) + (i & 7) : 14 * ((i - 24) / 6) + 8 + (i - 24) % 6; }
constexpr int MB_X = BAR_OFF  , MB_M = BAR_OFF + 16  , MB_IN = BAR_OFF + 40  , MB_QC = BAR_OFF + 120, MB_H1 = BAR_OFF + 64,
              MB_KV = BAR_OFF + 72  , MB_FREE = BAR_OFF + 88  , MB_XD = BAR_OFF + 104  , MB_WO = BAR_OFF + 128;
constexpr float SCALE = 0.08838834764831845f;
constexpr float LOG2E = 1.4426950408889634f;
constexpr int A_THREADS = 384, A_CTAS = 112;

#define FRESH_LANE() int lane = lane_r; asm volatile("" : "+r"(lane)); const int g = lane >> 2, t = lane & 3; const uint32_t l16 = lane * 16; (void)g; (void)t; (void)l16
#define PIN(x) asm volatile("" ::"r"(x))
#define TS(i) do {} while (0)
#define TSV(i, cond, val) do {} while (0)

__global__ void __launch_bounds__(A_THREADS, 1)
rec_kernel(const __grid_constant__ CUtensorMap tmx, const bf16* __restrict__ mem0, const bf16* __restrict__ Wq,
           const bf16* __restrict__ Wk, const bf16* __restrict__ Wv, const bf16* __restrict__ Wo, const AuxArgs P) {
    extern __shared__ __align__(1024) unsigned char smem[];
    const uint32_t sb = __shfl_sync(0xffffffffu, smem_u32(smem), 0);
    const int tid = threadIdx.x, warp = __shfl_sync(0xffffffffu, tid >> 5, 0);
    const int lane = tid & 31;
    const int g = lane >> 2, t = lane & 3;
    uint32_t rank; asm volatile("mov.u32 %0, %%cluster_ctarank;" : "=r"(rank));
    const int cl = blockIdx.x >> 4;
    const int nh = cl < 4 ? 5 : 4;
    const int hl = rank / 3, role = rank - 3 * hl, tb = 3 * hl;
    const int head = (cl < 4 ? 5 * cl : 20 + 4 * (cl - 4)) + hl;
    const bool is_head = hl < nh;
    const int nown = 3 * nh;

    const int worker = cl < 4 ? cl : 4 + (cl - 4) * 4 + ((int)rank - 12);
    asm volatile("griddepcontrol.launch_dependents;");
    CAL(blockIdx.x, 0);
    if (tid == 0) {
        mbar_init(sb + MB_X, 1); mbar_init(sb + MB_X + 8, 1);
        for (int j = 0; j < 3; j++) mbar_init(sb + MB_M + 8 * j, 1);
        mbar_init(sb + MB_IN, 1); mbar_init(sb + MB_IN + 8, 1); mbar_init(sb + MB_IN + 16, 1); mbar_init(sb + MB_QC, 3);
        mbar_init(sb + MB_H1, 1); mbar_init(sb + MB_KV, 1); mbar_init(sb + MB_KV + 8, 1);
        mbar_init(sb + MB_FREE, 2); mbar_init(sb + MB_FREE + 8, 2); mbar_init(sb + MB_XD, 8); mbar_init(sb + MB_XD + 8, 8); mbar_init(sb + MB_WO, 96);
        asm volatile("fence.mbarrier_init.release.cluster;" ::: "memory");
        fence_async_smem();
        mbar_expect(sb + MB_X, 40960); mbar_expect(sb + MB_X + 8, 40960);
        if (!is_head) aux_init(sb);
    }
    __syncthreads();
    cluster_sync();
    const uint16_t tmask = (uint16_t)(7u << tb);
    if (tid == 0 && is_head) {
        for (int n = 0; n < 2; n++)
            for (int kb = role; kb < 10; kb += 3) tma3d_mc(sb + XT_OFF + n * 40960 + kb * 4096, &tmx, 0, 32 * n, kb, sb + MB_X + 8 * n, tmask);
    }

    if (warp < 8) {
        asm volatile("setmaxnreg.inc.sync.aligned.u32 224;");
        if (is_head) {
        const int lane_r = __shfl_sync(0xffffffffu, tid & 31, tid & 31);
        const int wg = warp >> 2, w = warp & 3;
        uint32_t A[40][4];
        {
            const bf16* W = role == 0 ? Wq : (role == 1 ? Wk : Wv);
            const bf16* wp = W + (size_t)(2 * t) * 4096 + head * 128 + 16 * warp + 2 * g;
#pragma unroll
            for (int ks = 0; ks < 40; ks++) {
                A[ks][0] = __ldg((const uint32_t*)(wp + (size_t)(16 * ks) * 4096));
                A[ks][1] = __ldg((const uint32_t*)(wp + (size_t)(16 * ks + 1) * 4096));
                A[ks][2] = __ldg((const uint32_t*)(wp + (size_t)(16 * ks + 8) * 4096));
                A[ks][3] = __ldg((const uint32_t*)(wp + (size_t)(16 * ks + 9) * 4096));
            }
#pragma unroll
            for (int ks = 0; ks < 40; ks++) {
                const uint32_t r0 = A[ks][0], r1 = A[ks][1], r2 = A[ks][2], r3 = A[ks][3];
                A[ks][0] = __byte_perm(r0, r1, 0x5410); A[ks][1] = __byte_perm(r0, r1, 0x7632);
                A[ks][2] = __byte_perm(r2, r3, 0x5410); A[ks][3] = __byte_perm(r2, r3, 0x7632);
            }
        }

        auto xproj = [&](int n) {
            const int st = n & 1;
            FRESH_LANE();
            const uint32_t a = sb + (role == 0 ? (st ? EX2_OFF : EX_OFF) : kv_off(role, role, n)) + (8 * (lane >> 4) + (lane & 7)) * KV_STRIDE + 32 * warp + ((lane >> 3) & 1) * 16;
            PIN(a);
            if (role == 0) { if (n >= 2) mbar_wait_u(sb + MB_QC, st); }
            else if (n >= 3) mbar_wait_u(sb + MB_FREE + 8 * ((n - 3) & 1), ((n - 3) >> 1) & 1);
            mbar_wait_u(sb + MB_X + 8 * st, (n >> 1) & 1);
            float acc[16];
            const uint32_t d0 = __shfl_sync(0xffffffffu, desc_sw128(sb + XT_OFF + st * 40960), 0);
            WG_FENCE();
#pragma unroll
            for (int ks = 0; ks < 40; ks++) wgmma_n32(acc, A[ks], d0 + (((ks >> 2) * 4096 + (ks & 3) * 32) >> 4), ks > 0);
            WG_COMMIT();
            WG_WAIT0();
            stsm4t(a, pack2(acc[0], acc[1]), pack2(acc[2], acc[3]), pack2(acc[4], acc[5]), pack2(acc[6], acc[7]));
            stsm4t(a + 16 * KV_STRIDE, pack2(acc[8], acc[9]), pack2(acc[10], acc[11]), pack2(acc[12], acc[13]), pack2(acc[14], acc[15]));
            fence_async_smem();
            __syncwarp();
            if (lane == 0) mbar_arrive(sb + MB_XD + 8 * st);
        };

        xproj(0);
        xproj(1);
#pragma unroll 1
        for (int s = 0; s < NSEG_; s++) {
            const int st = s & 1;
            if (warp == 4 && lane_r == 0) mbar_expect(sb + MB_H1, 6144);
            {
                float acc[4][4];
#pragma unroll
                for (int i = 0; i < 16; i++) ((float*)acc)[i] = 0.f;
                FRESH_LANE();
                const uint32_t mrd = sb + M_OFF + lane * 8;
                const uint32_t dl = sb + (role == 0 ? QF_OFF : (role == 1 ? KF_OFF : VF_OFF) + st * 2048) + warp * 256 + lane * 8;
                PIN(mrd); PIN(dl);
                mbar_wait_u(sb + MB_M, st);
                TS(0);
                uint2 b[40];
#pragma unroll
                for (int i = 0; i < 12; i++) b[i] = lds64(mrd + korder(i) * 256);
#pragma unroll
                for (int i = 0; i < 40; i++) {
                    if (i == LOOKW) {
                        mbar_wait_u(sb + MB_M + 8, st);
#pragma unroll
                        for (int k = 24; k < LOOKW + 12; k++) b[k] = lds64(mrd + korder(k) * 256);
                    }
                    if (i + 12 < 40 && (i + 12 < 24 || i >= LOOKW)) b[i + 12] = lds64(mrd + korder(i + 12) * 256);
                    mma16(acc[i & 3], A[korder(i)], b[i].x, b[i].y);
                }
                TS(1);
                uint32_t u0 = pack2((acc[0][0] + acc[1][0]) + (acc[2][0] + acc[3][0]), (acc[0][1] + acc[1][1]) + (acc[2][1] + acc[3][1]));
                uint32_t u1 = pack2((acc[0][2] + acc[1][2]) + (acc[2][2] + acc[3][2]), (acc[0][3] + acc[1][3]) + (acc[2][3] + acc[3][3]));
                if (role != 2) { u0 = movm(u0); u1 = movm(u1); }
#pragma unroll
                for (int r = 0; r < 3; r++) st_async8(mapa(dl, tb + r), u0, u1, mapa(sb + MB_H1, tb + r));
            }
            TS(2);
            if (s == NSEG_ - 1) break;
            if (s == 0) mbar_wait_u(sb + MB_WO, 0);
            uint32_t wa[8][4];
            const bool pair = wg || (w >= 2 && role != 2);
            const int tileB = wg ? 8 + w : 10 + w;
            int wA, rA, wB, rB;
            tile_owner(role, warp, nown, wA, rA); tile_owner(role, tileB, nown, wB, rB);
            uint32_t wl, inA, inB;
            {
                FRESH_LANE();
                wl = sb + WO_OFF + ((lane & 7) + (lane >> 4) * 8) * WO_STRIDE + ((lane >> 3) & 1) * 16;
                inA = mapa(sb + IN_OFF + wA * 1280 + hl * 256, rA); inB = mapa(sb + IN_OFF + wB * 1280 + hl * 256, rB);
                PIN(wl);
            }
            if (wg) {
                FRESH_LANE();
#pragma unroll
                for (int ks = 0; ks < 8; ks++) ldsm4t(wa[ks], wl + warp * 32 + ks * 16 * WO_STRIDE);
                if (w < 2) {
                    mbar_wait_u(sb + MB_H1, st);
                    if (lane == 0) {
                        if (w == 0) {
                            mbar_expect(sb + MB_M, 6144); mbar_expect(sb + MB_M + 8, 4096);
                        }
                        else {
                            for (int n = (s == 0 ? 2 : s + 3); n <= s + 3 && n < NSEG_; n++) {
                                mbar_expect(sb + MB_X + 8 * (n & 1), 40960);
                                for (int kb = role; kb < 10; kb += 3)
                                    tma3d_mc(sb + XT_OFF + (n & 1) * 40960 + kb * 4096, &tmx, 0, 32 * n, kb, sb + MB_X + 8 * (n & 1), tmask);
                            }
                        }
                    }
                    __syncwarp();
                }
            } else {
                FRESH_LANE();
                const uint32_t s_base = sb + M_OFF + role * 3584;
                const uint32_t r8 = (lane & 7) * KV_STRIDE;
                const int mt = w & 1, eh = w >> 1;
                mbar_wait_u(sb + MB_KV + 8 * st, (s >> 1) & 1);
                if (w == 3 && lane == 0) asm volatile("mbarrier.arrive.relaxed.cluster.shared::cluster.b64 _, [%0];" ::"r"(mapa(sb + MB_QC, tb)) : "memory");
                uint32_t vb[2][2][4];
                uint2 vm[2];
                {
                    const uint32_t ka = sb + kv_off(1, role, s) + eh * 128 + r8 + (16 * mt + ((lane >> 3) & 1) * 8) * KV_STRIDE + (lane >> 4) * 16;
                    const uint32_t fl = sb + lane * 8;
                    const uint32_t sw = s_base + eh * 1280 + mt * 64 + t * 320 + g * 4;
                    const uint32_t sm = s_base + 2560 + w * 256 + t * 64 + g * 4;
                    uint32_t a[4][4];
#pragma unroll
                    for (int k = 0; k < 4; k++) ldsm4(a[k], ka + k * 32);
                    const uint32_t va1 = sb + kv_off(2, role, s) + w * 64 + r8 + ((lane >> 3) & 1) * 8 * KV_STRIDE + (lane >> 4) * 16;
                    ldsm4t(vb[0][0], va1); ldsm4t(vb[0][1], va1 + 32);
                    ldsm4t(vb[1][0], va1 + 16 * KV_STRIDE); ldsm4t(vb[1][1], va1 + 16 * KV_STRIDE + 32);
                    PIN(fl); PIN(sw); PIN(sm);
                    mbar_wait_u(sb + MB_H1, st);
                    TS(3);
                    uint2 b[4], am[2], bm[2];
#pragma unroll
                    for (int k = 0; k < 4; k++) b[k] = lds64(fl + QF_OFF + (4 * eh + k) * 256);
#pragma unroll
                    for (int k = 0; k < 2; k++) { am[k] = lds64(fl + KF_OFF + st * 2048 + (2 * w + k) * 256); bm[k] = lds64(fl + QF_OFF + (2 * w + k) * 256); }
                    float c0[4] = {0, 0, 0, 0}, c1[4] = {0, 0, 0, 0}, c2[4] = {0, 0, 0, 0}, c3[4] = {0, 0, 0, 0};
                    mma16(c0, a[0], b[0].x, b[0].y); mma16(c1, a[1], b[1].x, b[1].y);
                    mma16r(c2, am[0].x, 0u, am[0].y, 0u, bm[0].x, bm[0].y);
                    mma16r(c3, am[1].x, 0u, am[1].y, 0u, bm[1].x, bm[1].y);
                    mma16(c0, a[2], b[2].x, b[2].y); mma16(c1, a[3], b[3].x, b[3].y);
                    sts32f(sm, c2[0] + c3[0]); sts32f(sm + 32, c2[1] + c3[1]);
                    sts32f(sw, c0[0] + c1[0]); sts32f(sw + 160, c0[1] + c1[1]);
                    sts32f(sw + 32, c0[2] + c1[2]); sts32f(sw + 160 + 32, c0[3] + c1[3]);
#pragma unroll
                    for (int k = 0; k < 2; k++) vm[k] = lds64(fl + VF_OFF + st * 2048 + (2 * w + k) * 256);
                }
                const uint32_t sr = s_base + g * 160 + t * 8;
                bar_sync(7, 128);
                TS(4);
                float sc[10];
                {
                    float2 m[4], p0[4], p1[4];
#pragma unroll
                    for (int j = 0; j < 4; j++) { p0[j] = lds64f(sr + j * 32); p1[j] = lds64f(sr + 1280 + j * 32); }
#pragma unroll
                    for (int j = 0; j < 4; j++) m[j] = lds64f(s_base + 2560 + j * 256 + lane * 8);
#pragma unroll
                    for (int j = 0; j < 4; j++) { sc[2 + 2 * j] = p0[j].x + p1[j].x; sc[3 + 2 * j] = p0[j].y + p1[j].y; }
                    sc[0] = (m[0].x + m[1].x) + (m[2].x + m[3].x); sc[1] = (m[0].y + m[1].y) + (m[2].y + m[3].y);
                }
                float mx = fmaxf(fmaxf(fmaxf(sc[2], sc[3]), fmaxf(sc[4], sc[5])), fmaxf(fmaxf(sc[6], sc[7]), fmaxf(sc[8], sc[9])));
                mx = fmaxf(mx, fmaxf(sc[0], sc[1]));
                mx = fmaxf(mx, __shfl_xor_sync(~0u, mx, 1)); mx = fmaxf(mx, __shfl_xor_sync(~0u, mx, 2));
                const float nm = -mx * (SCALE * LOG2E);
#pragma unroll
                for (int i = 0; i < 10; i++) sc[i] = ex2(fmaf(sc[i], SCALE * LOG2E, nm));
                uint32_t p[5];
#pragma unroll
                for (int j = 0; j < 5; j++) p[j] = pack2(sc[2 * j], sc[2 * j + 1]);
                float o[4][4];
#pragma unroll
                for (int i = 0; i < 16; i++) ((float*)o)[i] = 0.f;
#pragma unroll
                for (int n = 0; n < 4; n++) mma8(o[n], p[0], 0u, (n & 1) ? vm[n >> 1].y : vm[n >> 1].x);
#pragma unroll
                for (int n = 0; n < 4; n++) mma16r(o[n], p[1], 0u, p[2], 0u, vb[0][n >> 1][2 * (n & 1)], vb[0][n >> 1][2 * (n & 1) + 1]);
#pragma unroll
                for (int n = 0; n < 4; n++) mma16r(o[n], p[3], 0u, p[4], 0u, vb[1][n >> 1][2 * (n & 1)], vb[1][n >> 1][2 * (n & 1) + 1]);
                float sum = ((sc[0] + sc[1]) + (sc[2] + sc[3])) + ((sc[4] + sc[5]) + (sc[6] + sc[7])) + (sc[8] + sc[9]);
                sum += __shfl_xor_sync(~0u, sum, 1); sum += __shfl_xor_sync(~0u, sum, 2);
                const float inv = rcp(sum);
                sts128(sb + O_OFF + w * 512 + l16,
                       make_uint4(pack2(o[0][0] * inv, o[0][1] * inv), pack2(o[1][0] * inv, o[1][1] * inv),
                                  pack2(o[2][0] * inv, o[2][1] * inv), pack2(o[3][0] * inv, o[3][1] * inv)));
#pragma unroll
                for (int ks = 0; ks < 8; ks++) ldsm4t(wa[ks], wl + warp * 32 + ks * 16 * WO_STRIDE);
            }
            {
            FRESH_LANE();
            bar_sync(1, 256);
            TS(5);
            uint4 ob[4];
#pragma unroll
            for (int k = 0; k < 4; k++) ob[k] = lds128(sb + O_OFF + k * 512 + l16);
            float d[2][4];
#pragma unroll
            for (int i = 0; i < 8; i++) ((float*)d)[i] = 0.f;
#pragma unroll
            for (int k = 0; k < 4; k++) {
                mma16(d[0], wa[2 * k], ob[k].x, ob[k].y); mma16(d[1], wa[2 * k + 1], ob[k].z, ob[k].w);
                if (pair) { ldsm4t(wa[2 * k], wl + tileB * 32 + (2 * k) * 16 * WO_STRIDE); ldsm4t(wa[2 * k + 1], wl + tileB * 32 + (2 * k + 1) * 16 * WO_STRIDE); }
            }
            st_async8(inA + lane * 8, pack2(d[0][0] + d[1][0], d[0][1] + d[1][1]), pack2(d[0][2] + d[1][2], d[0][3] + d[1][3]), mapa(sb + MB_IN + 8 * wA, rA));
            if (pair) {
#pragma unroll
                for (int i = 0; i < 8; i++) ((float*)d)[i] = 0.f;
#pragma unroll
                for (int k = 0; k < 4; k++) { mma16(d[0], wa[2 * k], ob[k].x, ob[k].y); mma16(d[1], wa[2 * k + 1], ob[k].z, ob[k].w); }
                st_async8(inB + lane * 8, pack2(d[0][0] + d[1][0], d[0][1] + d[1][1]), pack2(d[0][2] + d[1][2], d[0][3] + d[1][3]), mapa(sb + MB_IN + 8 * wB, rB));
            }
            }
            TS(6);
            TSV(14, threadIdx.x == 224, clk());
            if (s + 2 < NSEG_) xproj(s + 2);
            TS(7);
        }
        if (warp == 0) { mbar_wait_u(sb + MB_H1, 1); mbar_wait_u(sb + MB_KV + 8, 1); mbar_wait_u(sb + MB_FREE, 1); mbar_wait_u(sb + MB_FREE + 8, 1); if (role == 0) mbar_wait_u(sb + MB_QC, 0); }
        }
        else aux_compute(P, smem, sb, worker, warp);
    } else {
      asm volatile("setmaxnreg.dec.sync.aligned.u32 56;");
      if (warp < 11) {
        const int cw = warp - 8, ct = cw * 32 + lane;
        const int q = is_head ? cw * nown + (int)rank : 36 + ((int)rank - 12) * 2 + cw, idx = is_head ? rank : 3 * cw;
        const bool own = is_head ? q < 40 : (nh == 4 && rank < 14 && cw < 2);
        const int T = slot_tile(q);
        if (own) st_rel8(&g_X[2][(T * 7 + cl) * 32 + lane], 0u, 0u);
        if (is_head) {
            uint2 mv[14];
#pragma unroll
            for (int j = 0; j < 14; j++) {
                const int p = min(ct + 96 * j, 1279), ks = p >> 5, l = p & 31;
                const uint32_t* mp = (const uint32_t*)(mem0 + (l >> 2) * DM_ + ks * 16 + 2 * (l & 3));
                mv[j] = make_uint2(__ldg(mp), __ldg(mp + 4));
            }
            const int nch = role == 2 ? 24 : 28;
            for (int r = cw; r < 128; r += 3) {
                if (lane < nch) cp_async16(sb + WO_OFF + r * WO_STRIDE + lane * 16, Wo + (size_t)(head * 128 + eperm(r)) * DM_ + role * 224 + lane * 8);
            }
            asm volatile("cp.async.mbarrier.arrive.noinc.shared.b64 [%0];" ::"r"(sb + MB_WO) : "memory");
#pragma unroll
            for (int j = 0; j < 14; j++) {
                const int p = min(ct + 96 * j, 1279);
                sts64(sb + M_OFF + p * 8, mv[j].x, mv[j].y);
            }
            bar_sync(6, 96);
            if (ct == 0) { mbar_arrive(sb + MB_M); mbar_arrive(sb + MB_M + 8); }
        }
        __threadfence();
        const bool sender = is_head && cw == 2;
        auto send_x = [&](int n) {
            const int st = n & 1;
            mbar_wait_u(sb + MB_XD + 8 * st, (n >> 1) & 1);
            if (n >= 1) mbar_wait_u(sb + MB_H1, (n - 1) & 1);
            if (n >= 2) mbar_wait_u(sb + MB_FREE + 8 * st, ((n - 2) >> 1) & 1);
            const int a0 = (2 * n) % 3, a1 = (2 * n + 1) % 3;
            const uint32_t mbkv = sb + MB_KV + 8 * st, qs = sb + (st ? EX2_OFF : EX_OFF);
            if (lane == 0) {
                if (role == 0) {
                    if (a0 != 0) bulk_s2s(mapa(sb + QX_OFF + st * QX_BYTES, tb + a0), qs, QX_BYTES, mapa(mbkv, tb + a0));
                    if (a1 != 0) bulk_s2s(mapa(sb + QX_OFF + st * QX_BYTES, tb + a1), qs + QX_BYTES, QX_BYTES, mapa(mbkv, tb + a1));
                } else {
                    const uint32_t src = sb + kv_off(role, role, n), dst = sb + kv_off(role, 0, n);
                    bulk_s2s(mapa(dst, tb), src, XB_BYTES, mapa(mbkv, tb));
                    bulk_s2s(mapa(dst, tb + 3 - role), src, XB_BYTES, mapa(mbkv, tb + 3 - role));
                }
            }
            if (role == 0 && (a0 == 0 || a1 == 0)) {
                const uint32_t src = qs + (a0 == 0 ? 0 : QX_BYTES);
                for (int i = lane; i < QX_BYTES / 16; i += 32) sts128(sb + QX_OFF + st * QX_BYTES + i * 16, lds128(src + i * 16));
            }
            __syncwarp();
            if (lane == 0) mbar_expect(mbkv, (role == 0 ? 2 * XB_BYTES : XB_BYTES) + (role != 0 && (a0 == role || a1 == role) ? QX_BYTES : 0));
            __syncwarp();
        };
        if (sender) send_x(0);
        if (own || sender) {
            const uint32_t mdst = sb + M_OFF + T * 256 + lane * 8;
            const uint32_t mbar = sb + MB_M + (q < 16 ? 8 : 0);
            if (own && lane == 0) mbar_expect(sb + MB_IN + 8 * cw, nh * 256);
#pragma unroll 1
            for (int s = 0; s < NSEG_ - 1; s++) {
                if (sender) send_x(s + 1);
                if (!own) continue;
                int lane_o = lane;
                asm volatile("" : "+r"(lane_o));
                uint2* xs = &g_X[s & 3][T * 7 * 32 + lane_o];
                uint2* xw = xs + cl * 32;
                const uint32_t ib = sb + IN_OFF + cw * 1280 + lane_o * 8;
                asm volatile("" ::"l"(xw), "r"(ib));
                mbar_wait_u(sb + MB_IN + 8 * cw, s & 1);
                TS(10);
                uint2 v[7];
                {
                    uint2 q5[5];
#pragma unroll
                    for (int h = 0; h < 4; h++) q5[h] = lds64(ib + h * 256);
                    q5[4] = make_uint2(0, 0);
                    if (nh == 5) q5[4] = lds64(ib + 1024);
#define SUM5(f, c) ((f(q5[0].c) + f(q5[1].c)) + (f(q5[2].c) + f(q5[3].c)) + f(q5[4].c))
                    const uint32_t o0 = nzw(pack2(SUM5(bflo, x), SUM5(bfhi, x))), o1 = nzw(pack2(SUM5(bflo, y), SUM5(bfhi, y)));
                    st_rel8(xw, o0, o1);
#pragma unroll
                    for (int c = 0; c < 7; c++) v[c] = c == cl ? make_uint2(o0, o1) : make_uint2(0, 0);
                }
                const int tw = clk();
                TS(11);
                if (lane == 0) mbar_expect(sb + MB_IN + 8 * cw, nh * 256);
                while (clk() - tw < DELAY_X) {}
                int guard = 0;
                while (true) {
                    uint32_t chk = 0xffffffffu;
#pragma unroll
                    for (int c = 0; c < 7; c++) if (min(v[c].x, v[c].y) == 0) v[c] = ld_poll8(xs + c * 32);
#pragma unroll
                    for (int c = 0; c < 7; c++) chk = min(chk, min(v[c].x, v[c].y));
                    if (!__any_sync(~0u, chk == 0)) break;
                    if (++guard > SPIN_LIMIT) { g_misc[2] = 2; break; }
                }
                TS(12);
#define SUM7(f, c) (((f(v[0].c) + f(v[1].c)) + (f(v[2].c) + f(v[3].c))) + ((f(v[4].c) + f(v[5].c)) + f(v[6].c)))
                const uint32_t b0 = movm(pack2(SUM7(bflo, x), SUM7(bfhi, x))), b1 = movm(pack2(SUM7(bflo, y), SUM7(bfhi, y)));
                int d = idx;
#pragma unroll
                for (int r = 0; r < 15; r++) {
                    if (r < 12 || nh == 5) st_async8(mapa(mdst, d), b0, b1, mapa(mbar, d));
                    d = d + 1 == nown ? 0 : d + 1;
                }
                TS(13);
                TSV(15, threadIdx.x == 256, guard);
                if (s > 0) { st_rel8(&g_X[(s - 1) & 3][(T * 7 + cl) * 32 + lane_o], 0u, 0u); __threadfence(); }
            }
        }
        if (!is_head && (!aux_quiet(worker) || (cw == 2 && aux_vid(worker) == 25))) aux_final(P, worker, cw);
      } else if (is_head) {
        unsigned* cnt = &g_oxcnt[cl];
        int pending = -1;
#pragma unroll 1
        for (int task = role; task < 2 * NSEG_; task += 3) {
            const int s = task >> 1, mt = task & 1;
            const int st = s & 1;
            mbar_wait_u(sb + MB_KV + 8 * st, (s >> 1) & 1);
            mbar_wait_u(sb + MB_H1, st);
            TS(8);
            int lane = threadIdx.x & 31;
            asm volatile("" : "+r"(lane));
            const int g = lane >> 2, t = lane & 3;
            float sc[5][4];
#pragma unroll
            for (int i = 0; i < 20; i++) ((float*)sc)[i] = 0.f;
            const uint32_t r8 = (lane & 7) * KV_STRIDE;
            {
                const uint32_t qa = sb + QX_OFF + st * QX_BYTES + ((lane >> 3) & 1) * 8 * KV_STRIDE + r8 + (lane >> 4) * 16;
                const uint32_t ka = sb + kv_off(1, role, s) + r8 + ((lane >> 3) & 1) * 16 + (lane >> 4) * 8 * KV_STRIDE;
                const uint32_t kf = sb + KF_OFF + st * 2048 + lane * 8;
                uint32_t a[2][4], b0[2][4], b1[2][4]; uint2 bm[2];
                ldsm4(a[0], qa); bm[0] = lds64(kf); ldsm4(b0[0], ka); ldsm4(b1[0], ka + 16 * KV_STRIDE);
#pragma unroll
                for (int ks = 0; ks < 8; ks++) {
                    const int c = ks & 1, n = c ^ 1;
                    if (ks < 7) {
                        ldsm4(a[n], qa + (ks + 1) * 32); bm[n] = lds64(kf + (ks + 1) * 256);
                        ldsm4(b0[n], ka + (ks + 1) * 32); ldsm4(b1[n], ka + 16 * KV_STRIDE + (ks + 1) * 32);
                    }
                    mma16(sc[0], a[c], bm[c].x, bm[c].y);
                    mma16(sc[1], a[c], b0[c][0], b0[c][1]); mma16(sc[2], a[c], b0[c][2], b0[c][3]);
                    if (mt) { mma16(sc[3], a[c], b1[c][0], b1[c][1]); mma16(sc[4], a[c], b1[c][2], b1[c][3]); }
                }
            }
            if (pending >= 0) { if (lane == 0) red_rel(cnt + pending * 8, 1); pending = -1; __syncwarp(); }
            uint32_t p[5][2];
#pragma unroll
            for (int h = 0; h < 2; h++) {
                const int lim = 8 + 16 * mt + g + 8 * h - 2 * t;
                float mx = -3.0e38f;
#pragma unroll
                for (int j = 0; j < 5; j++) {
                    uint32_t r1 = pack2(sc[j][2 * h], sc[j][2 * h + 1]);
                    r1 = pack2(bflo(r1) * SCALE, bfhi(r1) * SCALE);
                    const float v0 = (8 * j <= lim) ? bflo(r1) : -1.0e9f, v1 = (8 * j + 1 <= lim) ? bfhi(r1) : -1.0e9f;
                    sc[j][2 * h] = v0; sc[j][2 * h + 1] = v1; mx = fmaxf(mx, fmaxf(v0, v1));
                }
                mx = fmaxf(mx, __shfl_xor_sync(~0u, mx, 1)); mx = fmaxf(mx, __shfl_xor_sync(~0u, mx, 2));
                float sum = 0.f;
#pragma unroll
                for (int j = 0; j < 5; j++) {
#pragma unroll
                    for (int i = 0; i < 2; i++) { float e = ex2((sc[j][2 * h + i] - mx) * LOG2E); sc[j][2 * h + i] = e; sum += e; }
                }
                sum += __shfl_xor_sync(~0u, sum, 1); sum += __shfl_xor_sync(~0u, sum, 2);
                const float inv = rcp(sum);
#pragma unroll
                for (int j = 0; j < 5; j++) p[j][h] = pack2(sc[j][2 * h] * inv, sc[j][2 * h + 1] * inv);
            }
            uint32_t* og = (uint32_t*)(g_ox + (size_t)(s * NH_ + head) * 512) + (16 * mt + g) * 32 + t;
            const uint32_t va = sb + kv_off(2, role, s) + r8 + ((lane >> 3) & 1) * 8 * KV_STRIDE + (lane >> 4) * 16;
            const uint32_t vf = sb + VF_OFF + st * 2048 + lane * 8;
            {
                uint32_t b0[2][4], b1[2][4]; uint2 bm[2];
                bm[0] = lds64(vf); ldsm4t(b0[0], va); ldsm4t(b1[0], va + 16 * KV_STRIDE);
#pragma unroll
                for (int np = 0; np < 8; np++) {
                    const int c = np & 1, nx = c ^ 1;
                    if (np < 7) { bm[nx] = lds64(vf + (np + 1) * 256); ldsm4t(b0[nx], va + (np + 1) * 32); ldsm4t(b1[nx], va + 16 * KV_STRIDE + (np + 1) * 32); }
                    float o[2][4] = {{0, 0, 0, 0}, {0, 0, 0, 0}};
                    mma8(o[0], p[0][0], p[0][1], bm[c].x); mma8(o[1], p[0][0], p[0][1], bm[c].y);
                    mma16r(o[0], p[1][0], p[1][1], p[2][0], p[2][1], b0[c][0], b0[c][1]);
                    mma16r(o[1], p[1][0], p[1][1], p[2][0], p[2][1], b0[c][2], b0[c][3]);
                    if (mt) {
                        mma16r(o[0], p[3][0], p[3][1], p[4][0], p[4][1], b1[c][0], b1[c][1]);
                        mma16r(o[1], p[3][0], p[3][1], p[4][0], p[4][1], b1[c][2], b1[c][3]);
                    }
#pragma unroll
                    for (int n = 0; n < 2; n++) {
                        const int ch = (2 * np + n) & 7;
                        int gx = g; asm volatile("" : "+r"(gx));
                        uint32_t* o2 = og + (np >> 2) * 1024 + ((ch ^ gx) << 2);
                        o2[0] = pack2(o[n][0], o[n][1]);
                        o2[256] = pack2(o[n][2], o[n][3]);
                    }
                }
            }
            __syncwarp();
            if (lane < 3) asm volatile("mbarrier.arrive.relaxed.cluster.shared::cluster.b64 _, [%0];" ::"r"(mapa(sb + MB_FREE + 8 * st, tb + lane)) : "memory");
            if (mt == 0 && task + 3 < 2 * NSEG_) pending = s;
            else if (lane == 0) red_rel(cnt + s * 8, 1);
            __syncwarp();
            TS(9);
        }
      }
      else if (lane == 0) aux_control(sb, worker);
    }
    __syncthreads();
    CAL(blockIdx.x, 1);
    cluster_sync();
}

__device__ bf16 f_mem[2][8 * DM_];
__device__ bf16 f_qkv[3][40 * 4096];
__device__ bf16 f_o[40 * 4096];
__global__ void fb_conv(const AuxArgs P) {
    __shared__ float u[S_], kk[S_];
    const int c = blockIdx.x;
    for (int t = threadIdx.x; t < S_; t += 256) {
        float a = 0.f;
        for (int tt = 0; tt < 4; tt++) { const int r = t + tt - 3; const float kv = r >= 0 ? __bfloat162float(P.Bk[(size_t)r * DM_ + c]) : 0.f; a = rbf(a + rbf(kv * __bfloat162float(P.shk[c * 4 + 3 - tt]))); }
        u[t] = rbf(a * __bfloat162float(P.Bv[(size_t)t * DM_ + c])); kk[t] = __bfloat162float(P.ssmk[(size_t)c * S_ + t]);
    }
    __syncthreads();
    const float D = __bfloat162float(P.ssmD[c]);
    for (int t = threadIdx.x; t < S_; t += 256) {
        float y = 0.f;
        for (int j = 0; j <= t; j++) y = fmaf(u[j], kk[t - j], y);
        g_b[(size_t)t * DM_ + c] = __float2bfloat16_rn(__bfloat162float(P.x[(size_t)t * DM_ + c]) * rbf(rbf(y) + rbf(u[t] * D)));
    }
}
__global__ void fb_proj(const bf16* x, const bf16* mem, const bf16* Wq, const bf16* Wk, const bf16* Wv, int s) {
    __shared__ bf16 h[40][DM_ / 2];
    const bf16* W = blockIdx.y == 0 ? Wq : (blockIdx.y == 1 ? Wk : Wv);
    const int col = blockIdx.x * 128 + threadIdx.x;
    float acc[40];
    for (int r = 0; r < 40; r++) acc[r] = 0.f;
    for (int half = 0; half < 2; half++) {
        __syncthreads();
        for (int i = threadIdx.x; i < 40 * 320; i += 128) { const int r = i / 320, d = i % 320 + half * 320; h[r][i % 320] = r < 8 ? mem[r * DM_ + d] : x[(size_t)(s * 32 + r - 8) * DM_ + d]; }
        __syncthreads();
        for (int d = 0; d < 320; d++) {
            const float wv = __bfloat162float(W[(size_t)(d + half * 320) * 4096 + col]);
#pragma unroll
            for (int r = 0; r < 40; r++) acc[r] = fmaf(__bfloat162float(h[r][d]), wv, acc[r]);
        }
    }
    for (int r = 0; r < 40; r++) f_qkv[blockIdx.y][r * 4096 + col] = __float2bfloat16_rn(acc[r]);
}
__global__ void fb_attn() {
    __shared__ float p[40][41];
    const int hb = blockIdx.x * 128;
    for (int i = threadIdx.x; i < 1600; i += 128) {
        const int q = i / 40, k = i % 40; float a = 0.f;
        for (int e = 0; e < 128; e++) a = fmaf(__bfloat162float(f_qkv[0][q * 4096 + hb + e]), __bfloat162float(f_qkv[1][k * 4096 + hb + e]), a);
        p[q][k] = (q < 8 || q >= k) ? rbf(rbf(a) * 0.08838834764831845f) : -1.0e9f;
    }
    __syncthreads();
    if (threadIdx.x < 40) {
        float* r = p[threadIdx.x]; float mx = r[0], sum = 0.f;
        for (int k = 1; k < 40; k++) mx = fmaxf(mx, r[k]);
        for (int k = 0; k < 40; k++) { r[k] = expf(r[k] - mx); sum += r[k]; }
        for (int k = 0; k < 40; k++) r[k] = rbf(r[k] / sum);
    }
    __syncthreads();
    for (int q = 0; q < 40; q++) {
        float a = 0.f;
        for (int k = 0; k < 40; k++) a = fmaf(p[q][k], __bfloat162float(f_qkv[2][k * 4096 + hb + threadIdx.x]), a);
        f_o[q * 4096 + hb + threadIdx.x] = __float2bfloat16_rn(a);
    }
}
__global__ void fb_out(const AuxArgs P, bf16* memn, int s) {
    __shared__ float o[4096]; __shared__ float red[128];
    const int r = blockIdx.x, c = blockIdx.y * 128 + threadIdx.x;
    for (int i = threadIdx.x; i < 4096; i += 128) o[i] = __bfloat162float(f_o[r * 4096 + i]);
    const int row = s * 32 + r - 8;
    float ga = 0.f;
    if (r >= 8) for (int d = threadIdx.x; d < DM_; d += 128) ga += rbf(__bfloat162float(P.x[(size_t)row * DM_ + d]) * __bfloat162float(P.gatew[d]));
    red[threadIdx.x] = ga;
    __syncthreads();
    float a = 0.f;
    for (int k = 0; k < 4096; k++) a = fmaf(o[k], __bfloat162float(P.Wo[(size_t)k * DM_ + c]), a);
    if (r < 8) { memn[r * DM_ + c] = __float2bfloat16_rn(a); return; }
    ga = 0.f; for (int i = 0; i < 128; i++) ga += red[i];
    const float gt = rbf(1.f / (1.f + expf(-rbf(ga)))), og = rbf(1.f - gt);
    P.out[(size_t)row * DM_ + c] = __float2bfloat16_rn(rbf(gt * rbf(a)) + rbf(og * __bfloat162float(g_b[(size_t)row * DM_ + c])));
}

typedef CUresult (*EncodeFn)(CUtensorMap*, CUtensorMapDataType, cuuint32_t, void*, const cuuint64_t*, const cuuint64_t*,
                             const cuuint32_t*, const cuuint32_t*, CUtensorMapInterleave, CUtensorMapSwizzle,
                             CUtensorMapL2promotion, CUtensorMapFloatOOBfill);

extern "C" void kernel_launch(void* const* d_in, const int* in_sizes, int n_in, void* d_out, int out_size) {
    const bf16* x = (const bf16*)d_in[0];
    const bf16* mem0 = (const bf16*)d_in[1];
    const bf16* Wq = (const bf16*)d_in[2];
    const bf16* Wk = (const bf16*)d_in[3];
    const bf16* Wv = (const bf16*)d_in[4];
    const bf16* Wo = (const bf16*)d_in[5];
    const bf16* Bk = (const bf16*)d_in[8];
    const bf16* Bv = (const bf16*)d_in[9];
    const bf16* shk = (const bf16*)d_in[10];
    const bf16* ssmk = (const bf16*)d_in[11];
    const bf16* ssmD = (const bf16*)d_in[12];
    const bf16* gatew = (const bf16*)d_in[13];

    static EncodeFn enc = nullptr;
    static int fast = -1;
    if (fast < 0) {
        void* fn = nullptr; cudaDriverEntryPointQueryResult qr;
        cudaGetDriverEntryPoint("cuTensorMapEncodeTiled", &fn, cudaEnableDefault, &qr);
        enc = (EncodeFn)fn;
        cudaFuncSetAttribute(rec_kernel, cudaFuncAttributeMaxDynamicSharedMemorySize, A_SMEM + 1024);
        cudaFuncSetAttribute(rec_kernel, cudaFuncAttributeNonPortableClusterSizeAllowed, 1);
        cudaFuncSetAttribute(aux_kernel, cudaFuncAttributeMaxDynamicSharedMemorySize, B_SMEM);
        cudaLaunchConfig_t qc = {};
        qc.gridDim = dim3(A_CTAS); qc.blockDim = dim3(A_THREADS); qc.dynamicSmemBytes = A_SMEM + 1024;
        cudaLaunchAttribute qa[1];
        qa[0].id = cudaLaunchAttributeClusterDimension; qa[0].val.clusterDim.x = 16; qa[0].val.clusterDim.y = 1; qa[0].val.clusterDim.z = 1;
        qc.attrs = qa; qc.numAttrs = 1;
        int ncl = 0, nsm = 0, dev = 0;
        cudaGetDevice(&dev);
        cudaDeviceGetAttribute(&nsm, cudaDevAttrMultiProcessorCount, dev);
        if (cudaOccupancyMaxActiveClusters(&ncl, rec_kernel, &qc) != cudaSuccess) { ncl = 0; cudaGetLastError(); }
        fast = (enc != nullptr && ncl >= 7 && nsm >= A_CTAS + NB_CTAS - N_SPARE + 1) ? 1 : 0;
    }
    if (!fast) {
        cudaStream_t fs = cudaStreamPerThread;
        AuxArgs FP = {x, Wo, Bk, Bv, shk, ssmk, ssmD, gatew, (bf16*)d_out};
        bf16* fm; cudaGetSymbolAddress((void**)&fm, f_mem);
        fb_conv<<<DM_, 256, 0, fs>>>(FP);
        for (int s = 0; s < NSEG_; s++) {
            fb_proj<<<dim3(32, 3), 128, 0, fs>>>(x, s == 0 ? mem0 : fm + (s & 1) * 8 * DM_, Wq, Wk, Wv, s);
            fb_attn<<<32, 128, 0, fs>>>();
            fb_out<<<dim3(40, 5), 128, 0, fs>>>(FP, fm + ((s + 1) & 1) * 8 * DM_, s);
        }
        return;
    }
    CUtensorMap tmx;
    {
        cuuint64_t dims[3] = {64, (cuuint64_t)S_, 10};
        cuuint64_t strides[2] = {DM_ * 2, 128};
        cuuint32_t box[3] = {64, 32, 1}, es[3] = {1, 1, 1};
        enc(&tmx, CU_TENSOR_MAP_DATA_TYPE_BFLOAT16, 3, (void*)x, dims, strides, box, es, CU_TENSOR_MAP_INTERLEAVE_NONE,
            CU_TENSOR_MAP_SWIZZLE_128B, CU_TENSOR_MAP_L2_PROMOTION_L2_256B, CU_TENSOR_MAP_FLOAT_OOB_FILL_NONE);
    }
    cudaStream_t st = cudaStreamPerThread;
    AuxArgs P = {x, Wo, Bk, Bv, shk, ssmk, ssmD, gatew, (bf16*)d_out};
    {
        cudaLaunchConfig_t ca = {};
        ca.gridDim = dim3(A_CTAS); ca.blockDim = dim3(A_THREADS); ca.dynamicSmemBytes = A_SMEM + 1024; ca.stream = st;
        cudaLaunchAttribute aa[1];
        aa[0].id = cudaLaunchAttributeClusterDimension; aa[0].val.clusterDim.x = 16; aa[0].val.clusterDim.y = 1; aa[0].val.clusterDim.z = 1;
        ca.attrs = aa; ca.numAttrs = 1;
        cudaLaunchKernelEx(&ca, rec_kernel, tmx, mem0, Wq, Wk, Wv, Wo, P);
    }
    cudaLaunchConfig_t cfg = {};
    cfg.gridDim = dim3(NB_CTAS - N_SPARE + 1);
    cfg.blockDim = dim3(B_THREADS); cfg.dynamicSmemBytes = B_SMEM; cfg.stream = st;
    cudaLaunchAttribute at[1];
    at[0].id = cudaLaunchAttributeProgrammaticStreamSerialization; at[0].val.programmaticStreamSerializationAllowed = 1;
    cfg.attrs = at; cfg.numAttrs = 1;
    cudaLaunchKernelEx(&cfg, aux_kernel, P);
}
```

```cpp
#include <cuda_runtime.h>
#include <cuda_bf16.h>
#include <cuda.h>
#include <stdint.h>

typedef __nv_bfloat16 bf16;

constexpr int S_ = 2048, DM_ = 640, NH_ = 32, NSEG_ = 64;
constexpr int NKG_ = 7, NCR_ = 5, NB_CTAS = NKG_ * NCR_;

#define DELAY_X 200
#define LOOKW 20
#define START_DELAY 10000
#define SPIN_LIMIT (1 << 13)
#define SPIN_FAIL(guard, code) (((++guard) & 1023) == 0 && (guard >= SPIN_LIMIT || *(volatile unsigned*)&g_misc[2] != 0) && ((g_misc[2] = (code)), true))

__device__ uint2 g_X[4][40 * 7 * 32];
__device__ uint4 g_ox[(size_t)NSEG_ * NH_ * 512];
__device__ float g_part[(size_t)NKG_ * S_ * DM_];
__device__ bf16 g_b[(size_t)S_ * DM_];
__device__ float g_gate[S_];
__device__ unsigned g_oxcnt[NSEG_ * 8];
__device__ unsigned g_pcnt[NSEG_ * 8];
__device__ unsigned g_misc[4];
#define CAL(b, i) do {} while (0)

__device__ __forceinline__ uint32_t smem_u32(const void* p) { return (uint32_t)__cvta_generic_to_shared(p); }
__device__ __forceinline__ void mbar_init(uint32_t mb, int cnt) { asm volatile("mbarrier.init.shared.b64 [%0], %1;" ::"r"(mb), "r"(cnt)); }
__device__ __forceinline__ void mbar_expect(uint32_t mb, int bytes) { asm volatile("mbarrier.arrive.expect_tx.shared.b64 _, [%0], %1;" ::"r"(mb), "r"(bytes) : "memory"); }
__device__ __forceinline__ void mbar_arrive(uint32_t mb) { asm volatile("mbarrier.arrive.shared.b64 _, [%0];" ::"r"(mb) : "memory"); }
__device__ __forceinline__ bool mbar_try(uint32_t mb, int parity) {
    uint32_t ok;
    asm volatile("{ .reg .pred p; mbarrier.try_wait.parity.shared.b64 p, [%1], %2; selp.u32 %0, 1, 0, p; }" : "=r"(ok) : "r"(mb), "r"(parity) : "memory");
    return ok;
}
__device__ __forceinline__ void mbar_wait(uint32_t mb, int parity) {
    int guard = 0;
    while (!mbar_try(mb, parity)) { if (SPIN_FAIL(guard, 1)) break; }
}
__device__ __forceinline__ void mbar_wait_u(uint32_t mb, int parity) {
    asm volatile("{ .reg .pred p; .reg .u32 c; mov.u32 c, 0;\n"
                 "WL%=: mbarrier.try_wait.parity.shared.b64 p, [%0], %1;\n"
                 "@p bra.uni WD%=;\n"
                 "add.u32 c, c, 1; setp.lt.u32 p, c, 16384;\n"
                 "@p bra.uni WL%=;\n"
                 "WD%=: }" ::"r"(mb), "r"(parity) : "memory");
}
__device__ __forceinline__ uint32_t movm(uint32_t a) { uint32_t d; asm volatile("movmatrix.sync.aligned.m8n8.trans.b16 %0, %1;" : "=r"(d) : "r"(a)); return d; }
__device__ __forceinline__ float ex2(float x) { float y; asm("ex2.approx.ftz.f32 %0, %1;" : "=f"(y) : "f"(x)); return y; }
__device__ __forceinline__ float rcp(float x) { float y; asm("rcp.approx.ftz.f32 %0, %1;" : "=f"(y) : "f"(x)); return y; }
__device__ __forceinline__ uint32_t mapa(uint32_t a, uint32_t r) { uint32_t o; asm volatile("mapa.shared::cluster.u32 %0, %1, %2;" : "=r"(o) : "r"(a), "r"(r)); return o; }
__device__ __forceinline__ uint4 ld_poll16(const void* p) { uint4 v; asm volatile("ld.relaxed.gpu.global.v4.u32 {%0,%1,%2,%3}, [%4];" : "=r"(v.x), "=r"(v.y), "=r"(v.z), "=r"(v.w) : "l"(p) : "memory"); return v; }
__device__ __forceinline__ void st_rel16(void* p, uint4 v) { asm volatile("st.relaxed.gpu.global.v4.u32 [%0], {%1,%2,%3,%4};" ::"l"(p), "r"(v.x), "r"(v.y), "r"(v.z), "r"(v.w) : "memory"); }
__device__ __forceinline__ void st_rel4(void* p, uint32_t v) { asm volatile("st.relaxed.gpu.global.u32 [%0], %1;" ::"l"(p), "r"(v) : "memory"); }
__device__ __forceinline__ unsigned ld_acq(const unsigned* p) { unsigned v; asm volatile("ld.acquire.gpu.global.u32 %0, [%1];" : "=r"(v) : "l"(p) : "memory"); return v; }
__device__ __forceinline__ void red_rel(unsigned* p, unsigned v) { asm volatile("red.release.gpu.global.add.u32 [%0], %1;" ::"l"(p), "r"(v) : "memory"); }
__device__ __forceinline__ void bar_sync(int id, int n) { asm volatile("bar.sync %0, %1;" ::"r"(id), "r"(n) : "memory"); }
__device__ __forceinline__ void st_async8(uint32_t dst, uint32_t a, uint32_t b, uint32_t mb) {
    asm volatile("st.async.weak.shared::cluster.mbarrier::complete_tx::bytes.v2.b32 [%0], {%1,%2}, [%3];" ::"r"(dst), "r"(a), "r"(b), "r"(mb) : "memory");
}
__device__ __forceinline__ void st_async16(uint32_t dst, uint32_t a, uint32_t b, uint32_t c, uint32_t d, uint32_t mb) {
    asm volatile("st.async.weak.shared::cluster.mbarrier::complete_tx::bytes.v4.b32 [%0], {%1,%2,%3,%4}, [%5];" ::"r"(dst), "r"(a), "r"(b), "r"(c), "r"(d), "r"(mb) : "memory");
}
__device__ __forceinline__ uint2 lds64(uint32_t a) { uint2 v; asm volatile("ld.shared.v2.u32 {%0,%1}, [%2];" : "=r"(v.x), "=r"(v.y) : "r"(a) : "memory"); return v; }
__device__ __forceinline__ uint2 ld_poll8(const void* p) { uint2 v; asm volatile("ld.relaxed.gpu.global.v2.u32 {%0,%1}, [%2];" : "=r"(v.x), "=r"(v.y) : "l"(p) : "memory"); return v; }
__device__ __forceinline__ void bulk_s2s(uint32_t dst, uint32_t src, uint32_t bytes, uint32_t mb) {
    asm volatile("cp.async.bulk.shared::cluster.shared::cta.mbarrier::complete_tx::bytes [%0], [%1], %2, [%3];" ::"r"(dst), "r"(src), "r"(bytes), "r"(mb) : "memory");
}
__device__ __forceinline__ void bulk_g2s(uint32_t dst, const void* src, uint32_t bytes, uint32_t mb) {
    asm volatile("cp.async.bulk.shared::cluster.global.mbarrier::complete_tx::bytes [%0], [%1], %2, [%3];" ::"r"(dst), "l"(src), "r"(bytes), "r"(mb) : "memory");
}
__device__ __forceinline__ void tma3d(uint32_t dst, const CUtensorMap* tm, int c0, int c1, int c2, uint32_t mb) {
    asm volatile("cp.async.bulk.tensor.3d.shared::cluster.global.mbarrier::complete_tx::bytes [%0], [%1, {%3, %4, %5}], [%2];"
                 ::"r"(dst), "l"((uint64_t)tm), "r"(mb), "r"(c0), "r"(c1), "r"(c2) : "memory");
}
__device__ __forceinline__ void tma3d_mc(uint32_t dst, const CUtensorMap* tm, int c0, int c1, int c2, uint32_t mb, uint16_t mask) {
    asm volatile("cp.async.bulk.tensor.3d.shared::cluster.global.mbarrier::complete_tx::bytes.multicast::cluster [%0], [%1, {%3, %4, %5}], [%2], %6;"
                 ::"r"(dst), "l"((uint64_t)tm), "r"(mb), "r"(c0), "r"(c1), "r"(c2), "h"(mask) : "memory");
}
__device__ __forceinline__ void st_rel8(void* p, uint32_t a, uint32_t b) { asm volatile("st.relaxed.gpu.global.v2.u32 [%0], {%1,%2};" ::"l"(p), "r"(a), "r"(b) : "memory"); }
__device__ __forceinline__ void fence_async_smem() { asm volatile("fence.proxy.async.shared::cta;" ::: "memory"); }
__device__ __forceinline__ void fence_async_all() { asm volatile("fence.proxy.async;" ::: "memory"); }
__device__ __forceinline__ void cp_async16(uint32_t dst, const void* src) { asm volatile("cp.async.cg.shared.global [%0], [%1], 16;" ::"r"(dst), "l"(src) : "memory"); }
__device__ __forceinline__ void cluster_sync() { asm volatile("barrier.cluster.arrive.aligned; barrier.cluster.wait.aligned;" ::: "memory"); }
__device__ __forceinline__ int clk() { int c; asm volatile("mov.u32 %0, %%clock;" : "=r"(c)); return c; }

__device__ __forceinline__ void ldsm4(uint32_t* r, uint32_t a) { asm volatile("ldmatrix.sync.aligned.m8n8.x4.shared.b16 {%0,%1,%2,%3}, [%4];" : "=r"(r[0]), "=r"(r[1]), "=r"(r[2]), "=r"(r[3]) : "r"(a) : "memory"); }
__device__ __forceinline__ void ldsm2(uint32_t* r, uint32_t a) { asm volatile("ldmatrix.sync.aligned.m8n8.x2.shared.b16 {%0,%1}, [%2];" : "=r"(r[0]), "=r"(r[1]) : "r"(a) : "memory"); }
__device__ __forceinline__ void ldsm4t(uint32_t* r, uint32_t a) { asm volatile("ldmatrix.sync.aligned.m8n8.x4.trans.shared.b16 {%0,%1,%2,%3}, [%4];" : "=r"(r[0]), "=r"(r[1]), "=r"(r[2]), "=r"(r[3]) : "r"(a) : "memory"); }
__device__ __forceinline__ void ldsm2t(uint32_t* r, uint32_t a) { asm volatile("ldmatrix.sync.aligned.m8n8.x2.trans.shared.b16 {%0,%1}, [%2];" : "=r"(r[0]), "=r"(r[1]) : "r"(a) : "memory"); }
__device__ __forceinline__ void stsm4t(uint32_t a, uint32_t r0, uint32_t r1, uint32_t r2, uint32_t r3) {
    asm volatile("stmatrix.sync.aligned.m8n8.x4.trans.shared.b16 [%0], {%1,%2,%3,%4};" ::"r"(a), "r"(r0), "r"(r1), "r"(r2), "r"(r3) : "memory");
}
__device__ __forceinline__ uint4 lds128(uint32_t a) { uint4 v; asm volatile("ld.shared.v4.u32 {%0,%1,%2,%3}, [%4];" : "=r"(v.x), "=r"(v.y), "=r"(v.z), "=r"(v.w) : "r"(a) : "memory"); return v; }
__device__ __forceinline__ float2 lds64f(uint32_t a) { float2 v; asm volatile("ld.shared.v2.f32 {%0,%1}, [%2];" : "=f"(v.x), "=f"(v.y) : "r"(a) : "memory"); return v; }
__device__ __forceinline__ float lds32f(uint32_t a) { float v; asm volatile("ld.shared.f32 %0, [%1];" : "=f"(v) : "r"(a) : "memory"); return v; }
__device__ __forceinline__ uint32_t lds32(uint32_t a) { uint32_t v; asm volatile("ld.shared.u32 %0, [%1];" : "=r"(v) : "r"(a) : "memory"); return v; }
__device__ __forceinline__ void sts128(uint32_t a, uint4 v) { asm volatile("st.shared.v4.u32 [%0], {%1,%2,%3,%4};" ::"r"(a), "r"(v.x), "r"(v.y), "r"(v.z), "r"(v.w) : "memory"); }
__device__ __forceinline__ void sts128f(uint32_t a, float x, float y, float z, float w) { asm volatile("st.shared.v4.f32 [%0], {%1,%2,%3,%4};" ::"r"(a), "f"(x), "f"(y), "f"(z), "f"(w) : "memory"); }
__device__ __forceinline__ void sts64f(uint32_t a, float x, float y) { asm volatile("st.shared.v2.f32 [%0], {%1,%2};" ::"r"(a), "f"(x), "f"(y) : "memory"); }
__device__ __forceinline__ void sts64(uint32_t a, uint32_t x, uint32_t y) { asm volatile("st.shared.v2.u32 [%0], {%1,%2};" ::"r"(a), "r"(x), "r"(y) : "memory"); }
__device__ __forceinline__ void sts32f(uint32_t a, float x) { asm volatile("st.shared.f32 [%0], %1;" ::"r"(a), "f"(x) : "memory"); }

__device__ __forceinline__ void mma16(float* d, const uint32_t* a, uint32_t b0, uint32_t b1) {
    asm volatile("mma.sync.aligned.m16n8k16.row.col.f32.bf16.bf16.f32 {%0,%1,%2,%3}, {%4,%5,%6,%7}, {%8,%9}, {%0,%1,%2,%3};"
                 : "+f"(d[0]), "+f"(d[1]), "+f"(d[2]), "+f"(d[3]) : "r"(a[0]), "r"(a[1]), "r"(a[2]), "r"(a[3]), "r"(b0), "r"(b1));
}
__device__ __forceinline__ void mma16r(float* d, uint32_t a0, uint32_t a1, uint32_t a2, uint32_t a3, uint32_t b0, uint32_t b1) {
    asm volatile("mma.sync.aligned.m16n8k16.row.col.f32.bf16.bf16.f32 {%0,%1,%2,%3}, {%4,%5,%6,%7}, {%8,%9}, {%0,%1,%2,%3};"
                 : "+f"(d[0]), "+f"(d[1]), "+f"(d[2]), "+f"(d[3]) : "r"(a0), "r"(a1), "r"(a2), "r"(a3), "r"(b0), "r"(b1));
}
__device__ __forceinline__ void mma8(float* d, uint32_t a0, uint32_t a1, uint32_t b0) {
    asm volatile("mma.sync.aligned.m16n8k8.row.col.f32.bf16.bf16.f32 {%0,%1,%2,%3}, {%4,%5}, {%6}, {%0,%1,%2,%3};"
                 : "+f"(d[0]), "+f"(d[1]), "+f"(d[2]), "+f"(d[3]) : "r"(a0), "r"(a1), "r"(b0));
}
__device__ __forceinline__ void wgmma_n32(float* d, const uint32_t* a, uint32_t desc_lo, int sc) {
    asm volatile("{ .reg .pred p; .reg .b64 dd; setp.ne.b32 p, %21, 0; mov.b64 dd, {%20, 0x40000040};\n"
                 "wgmma.mma_async.sync.aligned.m64n32k16.f32.bf16.bf16 {%0,%1,%2,%3,%4,%5,%6,%7,%8,%9,%10,%11,%12,%13,%14,%15}, {%16,%17,%18,%19}, dd, p, 1, 1, 0; }\n"
                 : "+f"(d[0]), "+f"(d[1]), "+f"(d[2]), "+f"(d[3]), "+f"(d[4]), "+f"(d[5]), "+f"(d[6]), "+f"(d[7]),
                   "+f"(d[8]), "+f"(d[9]), "+f"(d[10]), "+f"(d[11]), "+f"(d[12]), "+f"(d[13]), "+f"(d[14]), "+f"(d[15])
                 : "r"(a[0]), "r"(a[1]), "r"(a[2]), "r"(a[3]), "r"(desc_lo), "r"(sc));
}
#define WG_FENCE() asm volatile("wgmma.fence.sync.aligned;" ::: "memory")
#define WG_COMMIT() asm volatile("wgmma.commit_group.sync.aligned;" ::: "memory")
#define WG_WAIT0() asm volatile("wgmma.wait_group.sync.aligned 0;" ::: "memory")
__device__ __forceinline__ uint32_t desc_sw128(uint32_t saddr) { return ((saddr & 0x3FFFF) >> 4) | (1u << 16); }
__device__ __forceinline__ uint32_t pack2(float lo, float hi) { __nv_bfloat162 h = __floats2bfloat162_rn(lo, hi); return *(uint32_t*)&h; }
__device__ __forceinline__ float bflo(uint32_t u) { return __uint_as_float(u << 16); }
__device__ __forceinline__ float bfhi(uint32_t u) { return __uint_as_float(u & 0xffff0000u); }
__device__ __forceinline__ float rbf(float x) { return __uint_as_float(pack2(0.f, x)); }
__device__ __forceinline__ uint32_t nzw(uint32_t u) { return u == 0 ? 0x80008000u : u; }
__device__ __forceinline__ uint32_t min4(uint4 v) { return min(min(v.x, v.y), min(v.z, v.w)); }
__device__ __forceinline__ void mbar_arrive_if(uint32_t mb, uint32_t c) {
    asm volatile("{ .reg .pred p; setp.ne.u32 p, %1, 0; @p mbarrier.arrive.shared.b64 _, [%0]; }" ::"r"(mb), "r"(c) : "memory");
}
__device__ __forceinline__ int eperm(int p) { return (p & ~15) + 2 * (p & 7) + ((p >> 3) & 1); }

constexpr int U_STRIDE = 136 * 48;
constexpr int KR_STRIDE = 2080 * 2 * 2;
constexpr int B_U_OFF = 0, B_KR_OFF = 8 * U_STRIDE, B_CONV_END = B_KR_OFF + 8 * KR_STRIDE;
constexpr int B_OX_STAGES = 3, B_OX_BYTES = 40960;
constexpr int B_BAR_OFF = B_OX_STAGES * B_OX_BYTES;
constexpr int B_SMEM = B_BAR_OFF + 128;

constexpr int B_THREADS = 384;

struct AuxArgs { const bf16 *x, *Wo, *Bk, *Bv, *shk, *ssmk, *ssmD, *gatew; bf16* out; };
constexpr int MBB_FULL = B_BAR_OFF, MBB_EMPTY = B_BAR_OFF + 24, MBB_ST = B_BAR_OFF + 48, MBB_GO = B_BAR_OFF + 80, MBB_FLAG = B_BAR_OFF + 96;

__device__ __forceinline__ void aux_init(uint32_t sb) {
    for (int i = 0; i < B_OX_STAGES; i++) { mbar_init(sb + MBB_FULL + 8 * i, 1); mbar_init(sb + MBB_EMPTY + 8 * i, 8); }
    for (int i = 0; i < 4; i++) mbar_init(sb + MBB_ST + 8 * i, 8);
    mbar_init(sb + MBB_GO, 8);
    fence_async_smem();
}
__device__ __forceinline__ bool mbar_test(uint32_t mb, int parity) {
    uint32_t ok;
    asm volatile("{ .reg .pred p; mbarrier.test_wait.parity.shared.b64 p, [%1], %2; selp.u32 %0, 1, 0, p; }" : "=r"(ok) : "r"(mb), "r"(parity) : "memory");
    return ok;
}
__device__ __forceinline__ bool aux_quiet(int p) { return p >= 4 && p < 16 && ((p - 4) & 2) == 0; }
__device__ __forceinline__ int aux_ord(int p) { return p < 4 ? p : (p < 16 ? 4 + ((p - 4) >> 2) * 2 + (p & 1) : p - 6); }
__device__ __forceinline__ int aux_vid(int p) {
    if (aux_quiet(p)) { const int qi = ((p - 4) >> 2) * 2 + (p & 1); return qi < 5 ? 30 + qi : 25; }
    const int o = aux_ord(p); return o < 25 ? o : o + 1;
}
constexpr unsigned AUX_EXITS = NB_CTAS + 29 * 3 + 1;
__device__ __forceinline__ bool aux_exit_last() {
    unsigned old; asm volatile("atom.acq_rel.gpu.global.add.u32 %0, [%1], 1;" : "=r"(old) : "l"(&g_misc[1]) : "memory");
    return old == AUX_EXITS - 1;
}
__device__ __forceinline__ void aux_reset(int i0, int step) {
    for (int i = i0; i < NSEG_ * 8; i += step) { g_oxcnt[i] = 0; g_pcnt[i] = 0; }
    if (i0 == 0) { g_misc[0] = 0; g_misc[1] = 0; }
}
__device__ __forceinline__ void aux_final(const AuxArgs& P, int p, int fw) {
    const int vid = aux_vid(p), kg = vid / NCR_, cr = vid % NCR_, nf = cr == 0 ? 5 : 6;
    const int lane = threadIdx.x & 31, c = cr * 128 + lane * 4;
    const int r0 = vid == 25 ? 30 : kg + nf * fw, rstep = vid == 25 ? 1 : 3 * nf, rend = (cr == 0 && vid != 25) ? 30 : 32;
    if (lane == 0) { int guard = 0; while (ld_acq(&g_misc[0]) < (unsigned)(NB_CTAS + 1)) { if (++guard > (1 << 20)) break; __nanosleep(500); } }
    __syncwarp();
    int ready = 0;
#pragma unroll 1
    for (int n = 0; n < NSEG_; n++) {
        if (n >= ready) {
            int guard = 0;
            while (true) {
                const bool ok = n + lane < NSEG_ && ld_acq(&g_pcnt[(n + lane) * 8 + cr]) >= (unsigned)NKG_;
                const unsigned m = __ballot_sync(~0u, ok);
                ready = n + (m == ~0u ? 32 : __ffs(~m) - 1);
                if (ready > n) break;
                if (++guard > (1 << 18)) { g_misc[2] = 6; ready = NSEG_; break; }
                __nanosleep(100);
            }
            __syncwarp();
        }
#pragma unroll 1
        for (int r = r0; r < rend; r += rstep) {
            const int row = n * 32 + r;
            float4 v[NKG_];
#pragma unroll
            for (int k = 0; k < NKG_; k++) v[k] = __ldcg((const float4*)(g_part + ((size_t)k * S_ + row) * DM_ + c));
            const float gt = __ldcg(&g_gate[row]), og = rbf(1.f - gt);
            const uint2 bv = __ldcg((const uint2*)(g_b + (size_t)row * DM_ + c));
            float4 a = v[0];
#pragma unroll
            for (int k = 1; k < NKG_; k++) { a.x += v[k].x; a.y += v[k].y; a.z += v[k].z; a.w += v[k].w; }
            uint2 o;
            o.x = pack2(rbf(gt * rbf(a.x)) + rbf(og * bflo(bv.x)), rbf(gt * rbf(a.y)) + rbf(og * bfhi(bv.x)));
            o.y = pack2(rbf(gt * rbf(a.z)) + rbf(og * bflo(bv.y)), rbf(gt * rbf(a.w)) + rbf(og * bfhi(bv.y)));
            *(uint2*)(P.out + (size_t)row * DM_ + c) = o;
        }
    }
    bool last = false;
    if (lane == 0) last = aux_exit_last();
    if (__shfl_sync(~0u, last, 0)) aux_reset(lane, 32);
}
__device__ __forceinline__ void aux_control(uint32_t sb, int p) {
    const int vid = aux_vid(p), kg = vid / NCR_, cr = vid % NCR_;
    const int h0 = kg < 4 ? kg * 5 : 20 + (kg - 4) * 4, nh = kg < 4 ? 5 : 4;
    { int guard = 0; while (!mbar_try(sb + MBB_GO, 0)) { if (++guard > (1 << 22)) break; } }
    red_rel(&g_misc[0], 1);
    if (p == NB_CTAS) return;
    int nl = 0, nr = 0, guard = 0;
    while (nr < NSEG_) {
        bool did = false;
        if (nl < NSEG_ && nl < nr + 4) {
            const int st = nl % B_OX_STAGES;
            if ((nl < B_OX_STAGES || mbar_test(sb + MBB_EMPTY + 8 * st, (nl / B_OX_STAGES - 1) & 1)) &&
                ld_acq(&g_oxcnt[nl * 8 + kg]) >= (unsigned)(2 * nh)) {
                fence_async_all();
                mbar_expect(sb + MBB_FULL + 8 * st, nh * 8192);
                bulk_g2s(sb + st * B_OX_BYTES, g_ox + (size_t)(nl * NH_ + h0) * 512, nh * 8192, sb + MBB_FULL + 8 * st);
                nl++; did = true;
            }
        }
        if (nr < nl && mbar_test(sb + MBB_ST + 8 * (nr & 3), (nr >> 2) & 1)) { red_rel(&g_pcnt[nr * 8 + cr], 1); nr++; did = true; }
        if (did) guard = 0;
        else { if (++guard > (1 << 17)) { g_misc[2] = 4; break; } __nanosleep(100); }
    }
    if (aux_exit_last()) aux_reset(0, 1);
}
__device__ __forceinline__ void aux_compute(const AuxArgs& P, unsigned char* smem, uint32_t sb, int cta, int warp) {
    const bf16* __restrict__ x = P.x; const bf16* __restrict__ Wo = P.Wo; const bf16* __restrict__ Bk = P.Bk; const bf16* __restrict__ Bv = P.Bv;
    const bf16* __restrict__ shk = P.shk; const bf16* __restrict__ ssmk = P.ssmk; const bf16* __restrict__ ssmD = P.ssmD;
    const bf16* __restrict__ gatew = P.gatew; bf16* __restrict__ out = P.out;
    const int tid = threadIdx.x, lane = tid & 31;
    const int g = lane >> 2, t = lane & 3;
    const int vid = aux_vid(cta), kg = vid / NCR_, cr = vid % NCR_;
    const bool quiet = aux_quiet(cta);
    const int ord = aux_ord(cta);
    const int h0 = kg < 4 ? kg * 5 : 20 + (kg - 4) * 4, nh = kg < 4 ? 5 : 4;
    const uint32_t mb_full = sb + MBB_FULL, mb_empty = sb + MBB_EMPTY, mb_st = sb + MBB_ST, mb_go = sb + MBB_GO;
    CAL(112 + cta, 0);
    if (cta == NB_CTAS) { const long long t0 = clock64(); while (clock64() - t0 < START_DELAY) __nanosleep(200); }
    else if (!quiet) {
        { const long long t0 = clock64(); while (clock64() - t0 < START_DELAY) __nanosleep(200); }
        uint32_t wv[10];
#pragma unroll
        for (int i = 0; i < 10; i++) wv[i] = __ldg((const uint32_t*)gatew + lane + 32 * i);
        uint32_t xv[9][10];
#pragma unroll
        for (int j = 0; j < 9; j++) {
            const int r = min(ord * 8 + warp + j * 232, S_ - 1);
#pragma unroll
            for (int i = 0; i < 10; i++) xv[j][i] = __ldg((const uint32_t*)(x + (size_t)r * DM_) + lane + 32 * i);
        }
#pragma unroll
        for (int j = 0; j < 9; j++) {
            const int r = ord * 8 + warp + j * 232;
            float acc = 0.f;
#pragma unroll
            for (int i = 0; i < 10; i++) acc += rbf(bflo(xv[j][i]) * bflo(wv[i])) + rbf(bfhi(xv[j][i]) * bfhi(wv[i]));
#pragma unroll
            for (int o = 16; o; o >>= 1) acc += __shfl_xor_sync(~0u, acc, o);
            if (lane == 0 && r < S_) g_gate[r] = rbf(1.f / (1.f + __expf(-rbf(acc))));
        }
    }

    int item0, nitem;
    if (cta >= 16) { item0 = 3 * (cta - 16); nitem = 3; }
    else { item0 = 60 + 2 * ord; nitem = quiet ? 0 : 2; }
    for (int item = item0; item < item0 + nitem; item++) {
        const int c0 = item * 8;
        bar_sync(1, 256);
        for (int i = tid; i < 8 * 24; i += 256) sts128(sb + B_U_OFF + (i / 24) * U_STRIDE + (i % 24) * 16, make_uint4(0, 0, 0, 0));
        {
            const uint32_t krb = sb + B_KR_OFF + warp * KR_STRIDE;
            const bf16* kp = ssmk + (size_t)(c0 + warp) * S_;
            uint4 v[8]; uint32_t pv[8];
#pragma unroll
            for (int j = 0; j < 8; j++) {
                const int i = lane + 32 * j;
                v[j] = __ldg((const uint4*)kp + i);
                pv[j] = i > 0 ? __ldg((const uint32_t*)kp + 4 * i - 1) : 0u;
            }
#pragma unroll
            for (int j = 0; j < 8; j++) {
                const int i = lane + 32 * j;
                sts128(krb + (2040 - 8 * i) * 2, make_uint4(__byte_perm(v[j].w, 0, 0x1032), __byte_perm(v[j].z, 0, 0x1032),
                                                            __byte_perm(v[j].y, 0, 0x1032), __byte_perm(v[j].x, 0, 0x1032)));
                sts128(krb + 4160 + (2040 - 8 * i) * 2, make_uint4(__byte_perm(v[j].w, v[j].z, 0x7610), __byte_perm(v[j].z, v[j].y, 0x7610),
                                                                   __byte_perm(v[j].y, v[j].x, 0x7610), __byte_perm(v[j].x, pv[j], 0x7610)));
            }
            if (lane < 4) { sts128(krb + 4096 + lane * 16, make_uint4(0, 0, 0, 0)); sts128(krb + 4160 + 4096 + lane * 16, make_uint4(0, 0, 0, 0)); }
        }
        {
            float sh[8][4];
#pragma unroll
            for (int c = 0; c < 8; c++) {
                uint2 v = __ldg((const uint2*)(shk + (c0 + c) * 4));
                sh[c][0] = bflo(v.x); sh[c][1] = bfhi(v.x); sh[c][2] = bflo(v.y); sh[c][3] = bfhi(v.y);
            }
            const int t0 = tid * 8;
            uint4 kr[11], vr[8];
#pragma unroll
            for (int i = 0; i < 11; i++) { int r = t0 - 3 + i; kr[i] = r >= 0 ? __ldg((const uint4*)(Bk + (size_t)r * DM_ + c0)) : make_uint4(0, 0, 0, 0); }
#pragma unroll
            for (int i = 0; i < 8; i++) vr[i] = __ldg((const uint4*)(Bv + (size_t)(t0 + i) * DM_ + c0));
#pragma unroll
            for (int c = 0; c < 8; c++) {
                float res[8];
#pragma unroll
                for (int i = 0; i < 8; i++) {
                    float a = 0.f;
#pragma unroll
                    for (int tt = 0; tt < 4; tt++) {
                        uint32_t wd = ((const uint32_t*)&kr[i + tt])[c >> 1];
                        float kv_ = (c & 1) ? bfhi(wd) : bflo(wd);
                        a = rbf(a + rbf(kv_ * sh[c][3 - tt]));
                    }
                    uint32_t wd = ((const uint32_t*)&vr[i])[c >> 1];
                    res[i] = a * ((c & 1) ? bfhi(wd) : bflo(wd));
                }
                uint4 o = make_uint4(pack2(res[0], res[1]), pack2(res[2], res[3]), pack2(res[4], res[5]), pack2(res[6], res[7]));
                sts128(sb + B_U_OFF + c * U_STRIDE + (8 + (tid >> 1)) * 48 + (tid & 1) * 16, o);
            }
        }
        bar_sync(1, 256);
        {
            float acc[16][4];
#pragma unroll
            for (int i = 0; i < 64; i++) ((float*)acc)[i] = 0.f;
            const uint32_t kb = sb + B_KR_OFF + warp * KR_STRIDE + ((g & 1) ? (2047 - g + 2 * t) * 2 : 4160 + (2046 - g + 2 * t) * 2);
            const uint32_t ub = sb + B_U_OFF + warp * U_STRIDE + (8 + (lane & 7) + (lane >> 4) * 8) * 48 + ((lane >> 3) & 1) * 16;
#pragma unroll 1
            for (int r = 0; r < 8; r++) {
                uint32_t pa[16][3];
#pragma unroll
                for (int m = 0; m < 16; m++) {
                    const uint32_t a = kb - (16 * (r + 8 * m)) * 2;
                    pa[m][0] = lds32(a + 16); pa[m][1] = lds32(a); pa[m][2] = lds32(a - 16);
                }
#pragma unroll
                for (int d = 0; d < 16; d += 2) {
                    uint32_t b[4];
                    ldsm4(b, ub + (8 * d - r) * 48);
#pragma unroll
                    for (int m = 0; m < 16 - d; m++) mma16r(acc[m + d], pa[m][1], pa[m][2], pa[m][0], pa[m][1], b[0], b[1]);
#pragma unroll
                    for (int m = 0; m < 15 - d; m++) mma16r(acc[m + d + 1], pa[m][1], pa[m][2], pa[m][0], pa[m][1], b[2], b[3]);
                }
            }
            __syncwarp();
            const float Dv = __bfloat162float(ssmD[c0 + warp]);
            bf16* u = (bf16*)(smem + B_U_OFF + warp * U_STRIDE) + 8 * 24;
#pragma unroll
            for (int i = 0; i < 16; i++) {
#pragma unroll
                for (int q = 0; q < 4; q++) {
                    const int idx = (8 * i + 2 * t + (q & 1)) * 24 + g + (q >> 1) * 8;
                    const float kvv = __bfloat162float(u[idx]);
                    u[idx] = __float2bfloat16_rn(rbf(acc[i][q]) + rbf(kvv * Dv));
                }
            }
        }
        uint4 xv[8];
#pragma unroll
        for (int j = 0; j < 8; j++) xv[j] = __ldg((const uint4*)(x + (size_t)(tid + 256 * j) * DM_ + c0));
        bar_sync(1, 256);
#pragma unroll
        for (int j = 0; j < 8; j++) {
            const int r = tid + 256 * j;
            uint32_t o[4];
            const bf16* u = (const bf16*)(smem + B_U_OFF) + (8 + (r >> 4)) * 24 + (r & 15);
#pragma unroll
            for (int c = 0; c < 4; c++) {
                uint32_t wd = ((const uint32_t*)&xv[j])[c];
                o[c] = pack2(bflo(wd) * __bfloat162float(u[(2 * c) * (U_STRIDE / 2)]), bfhi(wd) * __bfloat162float(u[(2 * c + 1) * (U_STRIDE / 2)]));
            }
            *(uint4*)(g_b + (size_t)r * DM_ + c0) = make_uint4(o[0], o[1], o[2], o[3]);
        }
    }
    fence_async_smem();
    __syncwarp();
    if (lane == 0) mbar_arrive(mb_go);
    CAL(112 + cta, 1);
    if (cta == NB_CTAS) return;

    const int wg = warp >> 2, w = warp & 3;
    const int col = cr * 128 + wg * 64 + 16 * w + 2 * g;
    uint32_t A[40][4];
#pragma unroll
    for (int ks = 0; ks < 40; ks++) {
        const int hh = ks >> 3;
        uint32_t r[4] = {0, 0, 0, 0};
        if (hh < nh) {
#pragma unroll
            for (int i = 0; i < 4; i++) {
                const int p = (ks & 7) * 16 + 2 * t + (i & 1) + (i >> 1) * 8;
                r[i] = __ldg((const uint32_t*)(Wo + (size_t)((h0 + hh) * 128 + eperm(p)) * DM_ + col));
            }
        }
        A[ks][0] = __byte_perm(r[0], r[1], 0x5410); A[ks][1] = __byte_perm(r[0], r[1], 0x7632);
        A[ks][2] = __byte_perm(r[2], r[3], 0x5410); A[ks][3] = __byte_perm(r[2], r[3], 0x7632);
    }
    CAL(112 + cta, 2);
#pragma unroll 1
    for (int n = 0; n < NSEG_; n++) {
        const int st = n % B_OX_STAGES;
        { int guard = 0; while (!mbar_try(mb_full + 8 * st, (n / B_OX_STAGES) & 1)) { if (++guard > (1 << 20)) break; } }
        __syncwarp();
        float acc[16];
        const uint32_t d0 = __shfl_sync(0xffffffffu, desc_sw128(sb + st * B_OX_BYTES), 0);
        WG_FENCE();
#pragma unroll
        for (int ks = 0; ks < 32; ks++) wgmma_n32(acc, A[ks], d0 + (((ks >> 2) * 4096 + (ks & 3) * 32) >> 4), ks > 0);
        if (nh == 5) {
#pragma unroll
            for (int ks = 32; ks < 40; ks++) wgmma_n32(acc, A[ks], d0 + (((ks >> 2) * 4096 + (ks & 3) * 32) >> 4), 1);
        }
        WG_COMMIT();
        WG_WAIT0();
        if (lane == 0) mbar_arrive(mb_empty + 8 * st);
        float* pp = g_part + ((size_t)kg * S_ + n * 32) * DM_ + col;
#pragma unroll
        for (int j = 0; j < 4; j++) {
            *(float2*)(pp + (size_t)(8 * j + 2 * t) * DM_) = make_float2(acc[4 * j], acc[4 * j + 2]);
            *(float2*)(pp + (size_t)(8 * j + 2 * t + 1) * DM_) = make_float2(acc[4 * j + 1], acc[4 * j + 3]);
        }
        __syncwarp();
        if (lane == 0) mbar_arrive(mb_st + 8 * (n & 3));
    }
    CAL(112 + cta, 3);
}

constexpr int N_SPARE = 16;
__global__ void __launch_bounds__(B_THREADS, 1) aux_kernel(const AuxArgs P) {
    extern __shared__ __align__(1024) unsigned char smem[];
    const uint32_t sb = __shfl_sync(0xffffffffu, smem_u32(smem), 0);
    const int warp = __shfl_sync(0xffffffffu, threadIdx.x >> 5, 0);
    const int cta = N_SPARE + blockIdx.x;
    if (threadIdx.x == 0) aux_init(sb);
    __syncthreads();
    if (warp >= 8) {
        asm volatile("setmaxnreg.dec.sync.aligned.u32 56;");
        if (warp == 11) { if (threadIdx.x == 352) aux_control(sb, cta); }
        else if (cta < NB_CTAS) aux_final(P, cta, warp - 8);
    } else {
        asm volatile("setmaxnreg.inc.sync.aligned.u32 224;");
        aux_compute(P, smem, sb, cta, warp);
    }
}

constexpr int XT_OFF = 0, WO_OFF = 81920, WO_STRIDE = 464, KV_STRIDE = 272, XB_BYTES = 32 * KV_STRIDE, QX_BYTES = 16 * KV_STRIDE,
              K_OFF = 141312, V_OFF = K_OFF + 2 * XB_BYTES, EX_OFF = V_OFF + 2 * XB_BYTES  ,
              QX_OFF = EX_OFF + XB_BYTES, QF_OFF = QX_OFF + 2 * QX_BYTES, KF_OFF = QF_OFF + 2048, VF_OFF = KF_OFF + 4096,
              IN_OFF = VF_OFF + 4096, M_OFF = IN_OFF + 3840, EX2_OFF = M_OFF + 10240 + 512  ,
              BAR_OFF = EX2_OFF + XB_BYTES, A_SMEM = BAR_OFF + 144;
constexpr int O_OFF = QF_OFF;
__device__ __forceinline__ uint32_t kv_off(int which, int role, int n) {
    const int base = which == 1 ? K_OFF : V_OFF;
    if (which != role) return base + (n & 1) * XB_BYTES;
    const int j = n % 3;
    return j == 2 ? EX_OFF : base + j * XB_BYTES;
}
__device__ __forceinline__ void tile_owner(int r, int tau, int nown, int& gr, int& rk) {
    const int q = tau < 8 ? 16 + 8 * r + tau : 6 * r + tau - 8;
    gr = q >= 2 * nown ? 2 : (q >= nown ? 1 : 0);
    rk = q - gr * nown;
    if (q >= 3 * nown) { rk = 12 + ((q - 36) >> 1); gr = (q - 36) & 1; }
}
__device__ __forceinline__ int slot_tile(int q) { return q < 16 ? 14 * (q / 6) + 8 + q % 6 : 14 * ((q - 16) >> 3) + ((q - 16) & 7); }
__host__ __device__ constexpr int korder(int i) { return i < 24 ? 14 * (i >> 3) + (i & 7) : 14 * ((i - 24) / 6) + 8 + (i - 24) % 6; }
constexpr int MB_X = BAR_OFF  , MB_M = BAR_OFF + 16  , MB_IN = BAR_OFF + 40  , MB_QC = BAR_OFF + 120, MB_H1 = BAR_OFF + 64,
              MB_KV = BAR_OFF + 72  , MB_FREE = BAR_OFF + 88  , MB_XD = BAR_OFF + 104  , MB_WO = BAR_OFF + 128;
constexpr float SCALE = 0.08838834764831845f;
constexpr float LOG2E = 1.4426950408889634f;
constexpr int A_THREADS = 384, A_CTAS = 112;

#define FRESH_LANE() int lane = lane_r; asm volatile("" : "+r"(lane)); const int g = lane >> 2, t = lane & 3; const uint32_t l16 = lane * 16; (void)g; (void)t; (void)l16
#define PIN(x) asm volatile("" ::"r"(x))
#define TS(i) do {} while (0)
#define TSV(i, cond, val) do {} while (0)

__global__ void __launch_bounds__(A_THREADS, 1)
rec_kernel(const __grid_constant__ CUtensorMap tmx, const bf16* __restrict__ mem0, const bf16* __restrict__ Wq,
           const bf16* __restrict__ Wk, const bf16* __restrict__ Wv, const bf16* __restrict__ Wo, const AuxArgs P) {
    extern __shared__ __align__(1024) unsigned char smem[];
    const uint32_t sb = __shfl_sync(0xffffffffu, smem_u32(smem), 0);
    const int tid = threadIdx.x, warp = __shfl_sync(0xffffffffu, tid >> 5, 0);
    const int lane = tid & 31;
    const int g = lane >> 2, t = lane & 3;
    uint32_t rank; asm volatile("mov.u32 %0, %%cluster_ctarank;" : "=r"(rank));
    const int cl = blockIdx.x >> 4;
    const int nh = cl < 4 ? 5 : 4;
    const int hl = rank / 3, role = rank - 3 * hl, tb = 3 * hl;
    const int head = (cl < 4 ? 5 * cl : 20 + 4 * (cl - 4)) + hl;
    const bool is_head = hl < nh;
    const int nown = 3 * nh;

    const int n_late = ((int)rank < 16) + ((int)rank + nown < 16), n_early = 3 - n_late - ((int)rank + 2 * nown >= 40);
    const int worker = cl < 4 ? cl : 4 + (cl - 4) * 4 + ((int)rank - 12);
    asm volatile("griddepcontrol.launch_dependents;");
    CAL(blockIdx.x, 0);
    if (tid == 0) {
        mbar_init(sb + MB_X, 1); mbar_init(sb + MB_X + 8, 1);
        mbar_init(sb + MB_M, 1 + n_early); mbar_init(sb + MB_M + 8, 1 + n_late);
        mbar_init(sb + MB_IN, 1); mbar_init(sb + MB_IN + 8, 1); mbar_init(sb + MB_IN + 16, 1); mbar_init(sb + MB_QC, 3);
        mbar_init(sb + MB_H1, 9); mbar_init(sb + MB_KV, 1); mbar_init(sb + MB_KV + 8, 1);
        mbar_init(sb + MB_FREE, 2); mbar_init(sb + MB_FREE + 8, 2); mbar_init(sb + MB_XD, 8); mbar_init(sb + MB_XD + 8, 8); mbar_init(sb + MB_WO, 96);
        asm volatile("fence.mbarrier_init.release.cluster;" ::: "memory");
        fence_async_smem();
        mbar_expect(sb + MB_X, 40960); mbar_expect(sb + MB_X + 8, 40960);
        if (!is_head) aux_init(sb);
    }
    __syncthreads();
    cluster_sync();
    const uint16_t tmask = (uint16_t)(7u << tb);
    if (tid == 0 && is_head) {
        for (int n = 0; n < 2; n++)
            for (int kb = role; kb < 10; kb += 3) tma3d_mc(sb + XT_OFF + n * 40960 + kb * 4096, &tmx, 0, 32 * n, kb, sb + MB_X + 8 * n, tmask);
    }

    if (warp < 8) {
        asm volatile("setmaxnreg.inc.sync.aligned.u32 224;");
        if (is_head) {
        const int lane_r = __shfl_sync(0xffffffffu, tid & 31, tid & 31);
        const int wg = warp >> 2, w = warp & 3;
        uint32_t A[40][4];
        {
            const bf16* W = role == 0 ? Wq : (role == 1 ? Wk : Wv);
            const bf16* wp = W + (size_t)(2 * t) * 4096 + head * 128 + 16 * warp + 2 * g;
#pragma unroll
            for (int ks = 0; ks < 40; ks++) {
                A[ks][0] = __ldg((const uint32_t*)(wp + (size_t)(16 * ks) * 4096));
                A[ks][1] = __ldg((const uint32_t*)(wp + (size_t)(16 * ks + 1) * 4096));
                A[ks][2] = __ldg((const uint32_t*)(wp + (size_t)(16 * ks + 8) * 4096));
                A[ks][3] = __ldg((const uint32_t*)(wp + (size_t)(16 * ks + 9) * 4096));
            }
#pragma unroll
            for (int ks = 0; ks < 40; ks++) {
                const uint32_t r0 = A[ks][0], r1 = A[ks][1], r2 = A[ks][2], r3 = A[ks][3];
                A[ks][0] = __byte_perm(r0, r1, 0x5410); A[ks][1] = __byte_perm(r0, r1, 0x7632);
                A[ks][2] = __byte_perm(r2, r3, 0x5410); A[ks][3] = __byte_perm(r2, r3, 0x7632);
            }
        }

        auto xproj = [&](int n) {
            const int st = n & 1;
            FRESH_LANE();
            const uint32_t a = sb + (role == 0 ? (st ? EX2_OFF : EX_OFF) : kv_off(role, role, n)) + (8 * (lane >> 4) + (lane & 7)) * KV_STRIDE + 32 * warp + ((lane >> 3) & 1) * 16;
            PIN(a);
            if (role == 0) { if (n >= 2) mbar_wait_u(sb + MB_QC, st); }
            else if (n >= 3) mbar_wait_u(sb + MB_FREE + 8 * ((n - 3) & 1), ((n - 3) >> 1) & 1);
            mbar_wait_u(sb + MB_X + 8 * st, (n >> 1) & 1);
            float acc[16];
            const uint32_t d0 = __shfl_sync(0xffffffffu, desc_sw128(sb + XT_OFF + st * 40960), 0);
            WG_FENCE();
#pragma unroll
            for (int ks = 0; ks < 40; ks++) wgmma_n32(acc, A[ks], d0 + (((ks >> 2) * 4096 + (ks & 3) * 32) >> 4), ks > 0);
            WG_COMMIT();
            WG_WAIT0();
            stsm4t(a, pack2(acc[0], acc[1]), pack2(acc[2], acc[3]), pack2(acc[4], acc[5]), pack2(acc[6], acc[7]));
            stsm4t(a + 16 * KV_STRIDE, pack2(acc[8], acc[9]), pack2(acc[10], acc[11]), pack2(acc[12], acc[13]), pack2(acc[14], acc[15]));
            fence_async_smem();
            __syncwarp();
            if (lane == 0) mbar_arrive(sb + MB_XD + 8 * st);
        };

        xproj(0);
        xproj(1);
#pragma unroll 1
        for (int s = 0; s < NSEG_; s++) {
            const int st = s & 1;
            if (warp == 4 && lane_r == 0) mbar_expect(sb + MB_H1, 4096);
            {
                float acc[4][4];
#pragma unroll
                for (int i = 0; i < 16; i++) ((float*)acc)[i] = 0.f;
                FRESH_LANE();
                const uint32_t mrd = sb + M_OFF + lane * 8;
                const uint32_t dl = sb + (role == 0 ? QF_OFF : (role == 1 ? KF_OFF : VF_OFF) + st * 2048) + warp * 256 + lane * 8;
                PIN(mrd); PIN(dl);
                mbar_wait_u(sb + MB_M, st);
                TS(0);
                uint2 b[40];
#pragma unroll
                for (int i = 0; i < 12; i++) b[i] = lds64(mrd + korder(i) * 256);
#pragma unroll
                for (int i = 0; i < 40; i++) {
                    if (i == LOOKW) {
                        mbar_wait_u(sb + MB_M + 8, st);
#pragma unroll
                        for (int k = 24; k < LOOKW + 12; k++) b[k] = lds64(mrd + korder(k) * 256);
                    }
                    if (i + 12 < 40 && (i + 12 < 24 || i >= LOOKW)) b[i + 12] = lds64(mrd + korder(i + 12) * 256);
                    mma16(acc[i & 3], A[korder(i)], b[i].x, b[i].y);
                }
                TS(1);
                uint32_t u0 = pack2((acc[0][0] + acc[1][0]) + (acc[2][0] + acc[3][0]), (acc[0][1] + acc[1][1]) + (acc[2][1] + acc[3][1]));
                uint32_t u1 = pack2((acc[0][2] + acc[1][2]) + (acc[2][2] + acc[3][2]), (acc[0][3] + acc[1][3]) + (acc[2][3] + acc[3][3]));
                if (role != 2) { u0 = movm(u0); u1 = movm(u1); }
                {
                    const int p1 = tb + (role == 2 ? 0 : role + 1), p2 = tb + (role == 0 ? 2 : role - 1);
                    st_async8(mapa(dl, p1), u0, u1, mapa(sb + MB_H1, p1));
                    st_async8(mapa(dl, p2), u0, u1, mapa(sb + MB_H1, p2));
                    sts64(dl, u0, u1);
                    __syncwarp();
                    if (lane == 0) mbar_arrive(sb + MB_H1);
                }
            }
            TS(2);
            if (s == NSEG_ - 1) break;
            if (s == 0) mbar_wait_u(sb + MB_WO, 0);
            uint32_t wa[8][4];
            const bool pair = wg || (w >= 2 && role != 2);
            const int tileB = wg ? 8 + w : 10 + w;
            int wA, rA, wB, rB;
            tile_owner(role, warp, nown, wA, rA); tile_owner(role, tileB, nown, wB, rB);
            uint32_t wl, inA, inB;
            {
                FRESH_LANE();
                wl = sb + WO_OFF + ((lane & 7) + (lane >> 4) * 8) * WO_STRIDE + ((lane >> 3) & 1) * 16;
                inA = mapa(sb + IN_OFF + wA * 1280 + hl * 256, rA); inB = mapa(sb + IN_OFF + wB * 1280 + hl * 256, rB);
                PIN(wl);
            }
            if (wg) {
                FRESH_LANE();
#pragma unroll
                for (int ks = 0; ks < 8; ks++) ldsm4t(wa[ks], wl + warp * 32 + ks * 16 * WO_STRIDE);
                if (w < 2) {
                    mbar_wait_u(sb + MB_H1, st);
                    if (lane == 0) {
                        if (w == 0) {
                            mbar_expect(sb + MB_M, 6144 - 256 * n_early); mbar_expect(sb + MB_M + 8, 4096 - 256 * n_late);
                        }
                        else {
                            for (int n = (s == 0 ? 2 : s + 3); n <= s + 3 && n < NSEG_; n++) {
                                mbar_expect(sb + MB_X + 8 * (n & 1), 40960);
                                for (int kb = role; kb < 10; kb += 3)
                                    tma3d_mc(sb + XT_OFF + (n & 1) * 40960 + kb * 4096, &tmx, 0, 32 * n, kb, sb + MB_X + 8 * (n & 1), tmask);
                            }
                        }
                    }
                    __syncwarp();
                }
            } else {
                FRESH_LANE();
                const uint32_t s_base = sb + M_OFF + role * 3584;
                const uint32_t r8 = (lane & 7) * KV_STRIDE;
                const int mt = w & 1, eh = w >> 1;
                mbar_wait_u(sb + MB_KV + 8 * st, (s >> 1) & 1);
                if (w == 3 && lane == 0) asm volatile("mbarrier.arrive.relaxed.cluster.shared::cluster.b64 _, [%0];" ::"r"(mapa(sb + MB_QC, tb)) : "memory");
                uint32_t vb[2][2][4];
                uint2 vm[2];
                {
                    const uint32_t ka = sb + kv_off(1, role, s) + eh * 128 + r8 + (16 * mt + ((lane >> 3) & 1) * 8) * KV_STRIDE + (lane >> 4) * 16;
                    const uint32_t fl = sb + lane * 8;
                    const uint32_t sw = s_base + eh * 1280 + mt * 64 + t * 320 + g * 4;
                    const uint32_t sm = s_base + 2560 + w * 256 + t * 64 + g * 4;
                    uint32_t a[4][4];
#pragma unroll
                    for (int k = 0; k < 4; k++) ldsm4(a[k], ka + k * 32);
                    const uint32_t va1 = sb + kv_off(2, role, s) + w * 64 + r8 + ((lane >> 3) & 1) * 8 * KV_STRIDE + (lane >> 4) * 16;
                    ldsm4t(vb[0][0], va1); ldsm4t(vb[0][1], va1 + 32);
                    ldsm4t(vb[1][0], va1 + 16 * KV_STRIDE); ldsm4t(vb[1][1], va1 + 16 * KV_STRIDE + 32);
                    PIN(fl); PIN(sw); PIN(sm);
                    mbar_wait_u(sb + MB_H1, st);
                    TS(3);
                    uint2 b[4], am[2], bm[2];
#pragma unroll
                    for (int k = 0; k < 4; k++) b[k] = lds64(fl + QF_OFF + (4 * eh + k) * 256);
#pragma unroll
                    for (int k = 0; k < 2; k++) { am[k] = lds64(fl + KF_OFF + st * 2048 + (2 * w + k) * 256); bm[k] = lds64(fl + QF_OFF + (2 * w + k) * 256); }
                    float c0[4] = {0, 0, 0, 0}, c1[4] = {0, 0, 0, 0}, c2[4] = {0, 0, 0, 0}, c3[4] = {0, 0, 0, 0};
                    mma16(c0, a[0], b[0].x, b[0].y); mma16(c1, a[1], b[1].x, b[1].y);
                    mma16r(c2, am[0].x, 0u, am[0].y, 0u, bm[0].x, bm[0].y);
                    mma16r(c3, am[1].x, 0u, am[1].y, 0u, bm[1].x, bm[1].y);
                    mma16(c0, a[2], b[2].x, b[2].y); mma16(c1, a[3], b[3].x, b[3].y);
                    sts32f(sm, c2[0] + c3[0]); sts32f(sm + 32, c2[1] + c3[1]);
                    sts32f(sw, c0[0] + c1[0]); sts32f(sw + 160, c0[1] + c1[1]);
                    sts32f(sw + 32, c0[2] + c1[2]); sts32f(sw + 160 + 32, c0[3] + c1[3]);
#pragma unroll
                    for (int k = 0; k < 2; k++) vm[k] = lds64(fl + VF_OFF + st * 2048 + (2 * w + k) * 256);
                }
                const uint32_t sr = s_base + g * 160 + t * 8;
                bar_sync(7, 128);
                TS(4);
                float sc[10];
                {
                    float2 m[4], p0[4], p1[4];
#pragma unroll
                    for (int j = 0; j < 4; j++) { p0[j] = lds64f(sr + j * 32); p1[j] = lds64f(sr + 1280 + j * 32); }
#pragma unroll
                    for (int j = 0; j < 4; j++) m[j] = lds64f(s_base + 2560 + j * 256 + lane * 8);
#pragma unroll
                    for (int j = 0; j < 4; j++) { sc[2 + 2 * j] = p0[j].x + p1[j].x; sc[3 + 2 * j] = p0[j].y + p1[j].y; }
                    sc[0] = (m[0].x + m[1].x) + (m[2].x + m[3].x); sc[1] = (m[0].y + m[1].y) + (m[2].y + m[3].y);
                }
                float mx = fmaxf(fmaxf(fmaxf(sc[2], sc[3]), fmaxf(sc[4], sc[5])), fmaxf(fmaxf(sc[6], sc[7]), fmaxf(sc[8], sc[9])));
                mx = fmaxf(mx, fmaxf(sc[0], sc[1]));
                mx = fmaxf(mx, __shfl_xor_sync(~0u, mx, 1)); mx = fmaxf(mx, __shfl_xor_sync(~0u, mx, 2));
                const float nm = -mx * (SCALE * LOG2E);
#pragma unroll
                for (int i = 0; i < 10; i++) sc[i] = ex2(fmaf(sc[i], SCALE * LOG2E, nm));
                uint32_t p[5];
#pragma unroll
                for (int j = 0; j < 5; j++) p[j] = pack2(sc[2 * j], sc[2 * j + 1]);
                float o[4][4];
#pragma unroll
                for (int i = 0; i < 16; i++) ((float*)o)[i] = 0.f;
#pragma unroll
                for (int n = 0; n < 4; n++) mma8(o[n], p[0], 0u, (n & 1) ? vm[n >> 1].y : vm[n >> 1].x);
#pragma unroll
                for (int n = 0; n < 4; n++) mma16r(o[n], p[1], 0u, p[2], 0u, vb[0][n >> 1][2 * (n & 1)], vb[0][n >> 1][2 * (n & 1) + 1]);
#pragma unroll
                for (int n = 0; n < 4; n++) mma16r(o[n], p[3], 0u, p[4], 0u, vb[1][n >> 1][2 * (n & 1)], vb[1][n >> 1][2 * (n & 1) + 1]);
                float sum = ((sc[0] + sc[1]) + (sc[2] + sc[3])) + ((sc[4] + sc[5]) + (sc[6] + sc[7])) + (sc[8] + sc[9]);
                sum += __shfl_xor_sync(~0u, sum, 1); sum += __shfl_xor_sync(~0u, sum, 2);
                const float inv = rcp(sum);
                sts128(sb + O_OFF + w * 512 + l16,
                       make_uint4(pack2(o[0][0] * inv, o[0][1] * inv), pack2(o[1][0] * inv, o[1][1] * inv),
                                  pack2(o[2][0] * inv, o[2][1] * inv), pack2(o[3][0] * inv, o[3][1] * inv)));
#pragma unroll
                for (int ks = 0; ks < 8; ks++) ldsm4t(wa[ks], wl + warp * 32 + ks * 16 * WO_STRIDE);
            }
            {
            FRESH_LANE();
            bar_sync(1, 256);
            TS(5);
            uint4 ob[4];
#pragma unroll
            for (int k = 0; k < 4; k++) ob[k] = lds128(sb + O_OFF + k * 512 + l16);
            float d[2][4];
#pragma unroll
            for (int i = 0; i < 8; i++) ((float*)d)[i] = 0.f;
#pragma unroll
            for (int k = 0; k < 4; k++) {
                mma16(d[0], wa[2 * k], ob[k].x, ob[k].y); mma16(d[1], wa[2 * k + 1], ob[k].z, ob[k].w);
                if (pair) { ldsm4t(wa[2 * k], wl + tileB * 32 + (2 * k) * 16 * WO_STRIDE); ldsm4t(wa[2 * k + 1], wl + tileB * 32 + (2 * k + 1) * 16 * WO_STRIDE); }
            }
            st_async8(inA + lane * 8, pack2(d[0][0] + d[1][0], d[0][1] + d[1][1]), pack2(d[0][2] + d[1][2], d[0][3] + d[1][3]), mapa(sb + MB_IN + 8 * wA, rA));
            if (pair) {
#pragma unroll
                for (int i = 0; i < 8; i++) ((float*)d)[i] = 0.f;
#pragma unroll
                for (int k = 0; k < 4; k++) { mma16(d[0], wa[2 * k], ob[k].x, ob[k].y); mma16(d[1], wa[2 * k + 1], ob[k].z, ob[k].w); }
                st_async8(inB + lane * 8, pack2(d[0][0] + d[1][0], d[0][1] + d[1][1]), pack2(d[0][2] + d[1][2], d[0][3] + d[1][3]), mapa(sb + MB_IN + 8 * wB, rB));
            }
            }
            TS(6);
            TSV(14, threadIdx.x == 224, clk());
            if (s + 2 < NSEG_) xproj(s + 2);
            else mbar_wait_u(sb + MB_FREE + 8, 0);
            TS(7);
        }
        if (warp == 0) { mbar_wait_u(sb + MB_H1, 1); mbar_wait_u(sb + MB_KV + 8, 1); mbar_wait_u(sb + MB_FREE, 1); mbar_wait_u(sb + MB_FREE + 8, 1); if (role == 0) mbar_wait_u(sb + MB_QC, 0); }
        }
        else aux_compute(P, smem, sb, worker, warp);
    } else {
      asm volatile("setmaxnreg.dec.sync.aligned.u32 56;");
      if (warp < 11) {
        const int cw = warp - 8, ct = cw * 32 + lane;
        const int q = is_head ? cw * nown + (int)rank : 36 + ((int)rank - 12) * 2 + cw, idx = is_head ? rank : 3 * cw;
        const bool own = is_head ? q < 40 : (nh == 4 && rank < 14 && cw < 2);
        const int T = slot_tile(q);
        if (own) st_rel8(&g_X[2][(T * 7 + cl) * 32 + lane], 0u, 0u);
        if (is_head) {
            uint2 mv[14];
#pragma unroll
            for (int j = 0; j < 14; j++) {
                const int p = min(ct + 96 * j, 1279), ks = p >> 5, l = p & 31;
                const uint32_t* mp = (const uint32_t*)(mem0 + (l >> 2) * DM_ + ks * 16 + 2 * (l & 3));
                mv[j] = make_uint2(__ldg(mp), __ldg(mp + 4));
            }
            const int nch = role == 2 ? 24 : 28;
            for (int r = cw; r < 128; r += 3) {
                if (lane < nch) cp_async16(sb + WO_OFF + r * WO_STRIDE + lane * 16, Wo + (size_t)(head * 128 + eperm(r)) * DM_ + role * 224 + lane * 8);
            }
            asm volatile("cp.async.mbarrier.arrive.noinc.shared.b64 [%0];" ::"r"(sb + MB_WO) : "memory");
#pragma unroll
            for (int j = 0; j < 14; j++) {
                const int p = min(ct + 96 * j, 1279);
                sts64(sb + M_OFF + p * 8, mv[j].x, mv[j].y);
            }
            bar_sync(6, 96);
            if (ct == 0) {
                for (int j = 0; j <= n_early; j++) mbar_arrive(sb + MB_M);
                for (int j = 0; j <= n_late; j++) mbar_arrive(sb + MB_M + 8);
            }
        }
        __threadfence();
        const bool sender = is_head && cw == 2;
        auto send_x = [&](int n) {
            const int st = n & 1;
            mbar_wait_u(sb + MB_XD + 8 * st, (n >> 1) & 1);
            if (n >= 1) mbar_wait_u(sb + MB_H1, (n - 1) & 1);
            if (n >= 2) mbar_wait_u(sb + MB_FREE + 8 * st, ((n - 2) >> 1) & 1);
            const int a0 = (2 * n) % 3, a1 = (2 * n + 1) % 3;
            const uint32_t mbkv = sb + MB_KV + 8 * st, qs = sb + (st ? EX2_OFF : EX_OFF);
            if (lane == 0) {
                if (role == 0) {
                    if (a0 != 0) bulk_s2s(mapa(sb + QX_OFF + st * QX_BYTES, tb + a0), qs, QX_BYTES, mapa(mbkv, tb + a0));
                    if (a1 != 0) bulk_s2s(mapa(sb + QX_OFF + st * QX_BYTES, tb + a1), qs + QX_BYTES, QX_BYTES, mapa(mbkv, tb + a1));
                } else {
                    const uint32_t src = sb + kv_off(role, role, n), dst = sb + kv_off(role, 0, n);
                    bulk_s2s(mapa(dst, tb), src, XB_BYTES, mapa(mbkv, tb));
                    bulk_s2s(mapa(dst, tb + 3 - role), src, XB_BYTES, mapa(mbkv, tb + 3 - role));
                }
            }
            if (role == 0 && (a0 == 0 || a1 == 0)) {
                const uint32_t src = qs + (a0 == 0 ? 0 : QX_BYTES);
                for (int i = lane; i < QX_BYTES / 16; i += 32) sts128(sb + QX_OFF + st * QX_BYTES + i * 16, lds128(src + i * 16));
            }
            __syncwarp();
            if (lane == 0) mbar_expect(mbkv, (role == 0 ? 2 * XB_BYTES : XB_BYTES) + (role != 0 && (a0 == role || a1 == role) ? QX_BYTES : 0));
            __syncwarp();
        };
        if (sender) send_x(0);
        if (own || sender) {
            const uint32_t mdst = sb + M_OFF + T * 256 + lane * 8;
            const uint32_t mbar = sb + MB_M + (q < 16 ? 8 : 0);
            if (own && lane == 0) mbar_expect(sb + MB_IN + 8 * cw, nh * 256);
#pragma unroll 1
            for (int s = 0; s < NSEG_ - 1; s++) {
                if (sender) send_x(s + 1);
                if (!own) continue;
                int lane_o = lane;
                asm volatile("" : "+r"(lane_o));
                uint2* xs = &g_X[s & 3][T * 7 * 32 + lane_o];
                uint2* xw = xs + cl * 32;
                const uint32_t ib = sb + IN_OFF + cw * 1280 + lane_o * 8;
                asm volatile("" ::"l"(xw), "r"(ib));
                mbar_wait_u(sb + MB_IN + 8 * cw, s & 1);
                TS(10);
                uint2 v[7];
                {
                    uint2 q5[5];
#pragma unroll
                    for (int h = 0; h < 4; h++) q5[h] = lds64(ib + h * 256);
                    q5[4] = make_uint2(0, 0);
                    if (nh == 5) q5[4] = lds64(ib + 1024);
#define SUM5(f, c) ((f(q5[0].c) + f(q5[1].c)) + (f(q5[2].c) + f(q5[3].c)) + f(q5[4].c))
                    const uint32_t o0 = nzw(pack2(SUM5(bflo, x), SUM5(bfhi, x))), o1 = nzw(pack2(SUM5(bflo, y), SUM5(bfhi, y)));
                    st_rel8(xw, o0, o1);
#pragma unroll
                    for (int c = 0; c < 7; c++) v[c] = c == cl ? make_uint2(o0, o1) : make_uint2(0, 0);
                }
                const int tw = clk();
                TS(11);
                if (lane == 0) mbar_expect(sb + MB_IN + 8 * cw, nh * 256);
                while (clk() - tw < DELAY_X) {}
                int guard = 0;
                while (true) {
                    uint32_t chk = 0xffffffffu;
#pragma unroll
                    for (int c = 0; c < 7; c++) if (min(v[c].x, v[c].y) == 0) v[c] = ld_poll8(xs + c * 32);
#pragma unroll
                    for (int c = 0; c < 7; c++) chk = min(chk, min(v[c].x, v[c].y));
                    if (!__any_sync(~0u, chk == 0)) break;
                    if (++guard > SPIN_LIMIT) { g_misc[2] = 2; break; }
                }
                TS(12);
#define SUM7(f, c) (((f(v[0].c) + f(v[1].c)) + (f(v[2].c) + f(v[3].c))) + ((f(v[4].c) + f(v[5].c)) + f(v[6].c)))
                const uint32_t b0 = movm(pack2(SUM7(bflo, x), SUM7(bfhi, x))), b1 = movm(pack2(SUM7(bflo, y), SUM7(bfhi, y)));
                int d = idx;
                if (!is_head) st_async8(mapa(mdst, d), b0, b1, mapa(mbar, d));
#pragma unroll
                for (int r = 1; r < 15; r++) {
                    d = d + 1 == nown ? 0 : d + 1;
                    if (r < 12 || nh == 5) st_async8(mapa(mdst, d), b0, b1, mapa(mbar, d));
                }
                if (is_head) { sts64(mdst, b0, b1); __syncwarp(); if (lane == 0) mbar_arrive(mbar); }
                TS(13);
                TSV(15, threadIdx.x == 256, guard);
                if (s > 0) { st_rel8(&g_X[(s - 1) & 3][(T * 7 + cl) * 32 + lane_o], 0u, 0u); __threadfence(); }
            }
        }
        if (!is_head && (!aux_quiet(worker) || (cw == 2 && aux_vid(worker) == 25))) aux_final(P, worker, cw);
      } else if (is_head) {
        unsigned* cnt = &g_oxcnt[cl];
        int pending = -1;
#pragma unroll 1
        for (int task = role; task < 2 * NSEG_; task += 3) {
            const int s = task >> 1, mt = task & 1;
            const int st = s & 1;
            mbar_wait_u(sb + MB_KV + 8 * st, (s >> 1) & 1);
            mbar_wait_u(sb + MB_H1, st);
            TS(8);
            int lane = threadIdx.x & 31;
            asm volatile("" : "+r"(lane));
            const int g = lane >> 2, t = lane & 3;
            float sc[5][4];
#pragma unroll
            for (int i = 0; i < 20; i++) ((float*)sc)[i] = 0.f;
            const uint32_t r8 = (lane & 7) * KV_STRIDE;
            {
                const uint32_t qa = sb + QX_OFF + st * QX_BYTES + ((lane >> 3) & 1) * 8 * KV_STRIDE + r8 + (lane >> 4) * 16;
                const uint32_t ka = sb + kv_off(1, role, s) + r8 + ((lane >> 3) & 1) * 16 + (lane >> 4) * 8 * KV_STRIDE;
                const uint32_t kf = sb + KF_OFF + st * 2048 + lane * 8;
                uint32_t a[2][4], b0[2][4], b1[2][4]; uint2 bm[2];
                ldsm4(a[0], qa); bm[0] = lds64(kf); ldsm4(b0[0], ka); ldsm4(b1[0], ka + 16 * KV_STRIDE);
#pragma unroll
                for (int ks = 0; ks < 8; ks++) {
                    const int c = ks & 1, n = c ^ 1;
                    if (ks < 7) {
                        ldsm4(a[n], qa + (ks + 1) * 32); bm[n] = lds64(kf + (ks + 1) * 256);
                        ldsm4(b0[n], ka + (ks + 1) * 32); ldsm4(b1[n], ka + 16 * KV_STRIDE + (ks + 1) * 32);
                    }
                    mma16(sc[0], a[c], bm[c].x, bm[c].y);
                    mma16(sc[1], a[c], b0[c][0], b0[c][1]); mma16(sc[2], a[c], b0[c][2], b0[c][3]);
                    if (mt) { mma16(sc[3], a[c], b1[c][0], b1[c][1]); mma16(sc[4], a[c], b1[c][2], b1[c][3]); }
                }
            }
            if (pending >= 0) { if (lane == 0) red_rel(cnt + pending * 8, 1); pending = -1; __syncwarp(); }
            uint32_t p[5][2];
#pragma unroll
            for (int h = 0; h < 2; h++) {
                const int lim = 8 + 16 * mt + g + 8 * h - 2 * t;
                float mx = -3.0e38f;
#pragma unroll
                for (int j = 0; j < 5; j++) {
                    uint32_t r1 = pack2(sc[j][2 * h], sc[j][2 * h + 1]);
                    r1 = pack2(bflo(r1) * SCALE, bfhi(r1) * SCALE);
                    const float v0 = (8 * j <= lim) ? bflo(r1) : -1.0e9f, v1 = (8 * j + 1 <= lim) ? bfhi(r1) : -1.0e9f;
                    sc[j][2 * h] = v0; sc[j][2 * h + 1] = v1; mx = fmaxf(mx, fmaxf(v0, v1));
                }
                mx = fmaxf(mx, __shfl_xor_sync(~0u, mx, 1)); mx = fmaxf(mx, __shfl_xor_sync(~0u, mx, 2));
                float sum = 0.f;
#pragma unroll
                for (int j = 0; j < 5; j++) {
#pragma unroll
                    for (int i = 0; i < 2; i++) { float e = ex2((sc[j][2 * h + i] - mx) * LOG2E); sc[j][2 * h + i] = e; sum += e; }
                }
                sum += __shfl_xor_sync(~0u, sum, 1); sum += __shfl_xor_sync(~0u, sum, 2);
                const float inv = rcp(sum);
#pragma unroll
                for (int j = 0; j < 5; j++) p[j][h] = pack2(sc[j][2 * h] * inv, sc[j][2 * h + 1] * inv);
            }
            uint32_t* og = (uint32_t*)(g_ox + (size_t)(s * NH_ + head) * 512) + (16 * mt + g) * 32 + t;
            const uint32_t va = sb + kv_off(2, role, s) + r8 + ((lane >> 3) & 1) * 8 * KV_STRIDE + (lane >> 4) * 16;
            const uint32_t vf = sb + VF_OFF + st * 2048 + lane * 8;
            {
                uint32_t b0[2][4], b1[2][4]; uint2 bm[2];
                bm[0] = lds64(vf); ldsm4t(b0[0], va); ldsm4t(b1[0], va + 16 * KV_STRIDE);
#pragma unroll
                for (int np = 0; np < 8; np++) {
                    const int c = np & 1, nx = c ^ 1;
                    if (np < 7) { bm[nx] = lds64(vf + (np + 1) * 256); ldsm4t(b0[nx], va + (np + 1) * 32); ldsm4t(b1[nx], va + 16 * KV_STRIDE + (np + 1) * 32); }
                    float o[2][4] = {{0, 0, 0, 0}, {0, 0, 0, 0}};
                    mma8(o[0], p[0][0], p[0][1], bm[c].x); mma8(o[1], p[0][0], p[0][1], bm[c].y);
                    mma16r(o[0], p[1][0], p[1][1], p[2][0], p[2][1], b0[c][0], b0[c][1]);
                    mma16r(o[1], p[1][0], p[1][1], p[2][0], p[2][1], b0[c][2], b0[c][3]);
                    if (mt) {
                        mma16r(o[0], p[3][0], p[3][1], p[4][0], p[4][1], b1[c][0], b1[c][1]);
                        mma16r(o[1], p[3][0], p[3][1], p[4][0], p[4][1], b1[c][2], b1[c][3]);
                    }
#pragma unroll
                    for (int n = 0; n < 2; n++) {
                        const int ch = (2 * np + n) & 7;
                        int gx = g; asm volatile("" : "+r"(gx));
                        uint32_t* o2 = og + (np >> 2) * 1024 + ((ch ^ gx) << 2);
                        o2[0] = pack2(o[n][0], o[n][1]);
                        o2[256] = pack2(o[n][2], o[n][3]);
                    }
                }
            }
            __syncwarp();
            if (lane < 3) asm volatile("mbarrier.arrive.relaxed.cluster.shared::cluster.b64 _, [%0];" ::"r"(mapa(sb + MB_FREE + 8 * st, tb + lane)) : "memory");
            if (mt == 0 && task + 3 < 2 * NSEG_) pending = s;
            else if (lane == 0) red_rel(cnt + s * 8, 1);
            __syncwarp();
            TS(9);
        }
      }
      else if (lane == 0) aux_control(sb, worker);
    }
    __syncthreads();
    CAL(blockIdx.x, 1);
    cluster_sync();
}

__device__ bf16 f_mem[2][8 * DM_];
__device__ bf16 f_qkv[3][40 * 4096];
__device__ bf16 f_o[40 * 4096];
__global__ void fb_conv(const AuxArgs P) {
    __shared__ float u[S_], kk[S_];
    const int c = blockIdx.x;
    for (int t = threadIdx.x; t < S_; t += 256) {
        float a = 0.f;
        for (int tt = 0; tt < 4; tt++) { const int r = t + tt - 3; const float kv = r >= 0 ? __bfloat162float(P.Bk[(size_t)r * DM_ + c]) : 0.f; a = rbf(a + rbf(kv * __bfloat162float(P.shk[c * 4 + 3 - tt]))); }
        u[t] = rbf(a * __bfloat162float(P.Bv[(size_t)t * DM_ + c])); kk[t] = __bfloat162float(P.ssmk[(size_t)c * S_ + t]);
    }
    __syncthreads();
    const float D = __bfloat162float(P.ssmD[c]);
    for (int t = threadIdx.x; t < S_; t += 256) {
        float y = 0.f;
        for (int j = 0; j <= t; j++) y = fmaf(u[j], kk[t - j], y);
        g_b[(size_t)t * DM_ + c] = __float2bfloat16_rn(__bfloat162float(P.x[(size_t)t * DM_ + c]) * rbf(rbf(y) + rbf(u[t] * D)));
    }
}
__global__ void fb_proj(const bf16* x, const bf16* mem, const bf16* Wq, const bf16* Wk, const bf16* Wv, int s) {
    __shared__ bf16 h[40][DM_ / 2];
    const bf16* W = blockIdx.y == 0 ? Wq : (blockIdx.y == 1 ? Wk : Wv);
    const int col = blockIdx.x * 128 + threadIdx.x;
    float acc[40];
    for (int r = 0; r < 40; r++) acc[r] = 0.f;
    for (int half = 0; half < 2; half++) {
        __syncthreads();
        for (int i = threadIdx.x; i < 40 * 320; i += 128) { const int r = i / 320, d = i % 320 + half * 320; h[r][i % 320] = r < 8 ? mem[r * DM_ + d] : x[(size_t)(s * 32 + r - 8) * DM_ + d]; }
        __syncthreads();
        for (int d = 0; d < 320; d++) {
            const float wv = __bfloat162float(W[(size_t)(d + half * 320) * 4096 + col]);
#pragma unroll
            for (int r = 0; r < 40; r++) acc[r] = fmaf(__bfloat162float(h[r][d]), wv, acc[r]);
        }
    }
    for (int r = 0; r < 40; r++) f_qkv[blockIdx.y][r * 4096 + col] = __float2bfloat16_rn(acc[r]);
}
__global__ void fb_attn() {
    __shared__ float p[40][41];
    const int hb = blockIdx.x * 128;
    for (int i = threadIdx.x; i < 1600; i += 128) {
        const int q = i / 40, k = i % 40; float a = 0.f;
        for (int e = 0; e < 128; e++) a = fmaf(__bfloat162float(f_qkv[0][q * 4096 + hb + e]), __bfloat162float(f_qkv[1][k * 4096 + hb + e]), a);
        p[q][k] = (q < 8 || q >= k) ? rbf(rbf(a) * 0.08838834764831845f) : -1.0e9f;
    }
    __syncthreads();
    if (threadIdx.x < 40) {
        float* r = p[threadIdx.x]; float mx = r[0], sum = 0.f;
        for (int k = 1; k < 40; k++) mx = fmaxf(mx, r[k]);
        for (int k = 0; k < 40; k++) { r[k] = expf(r[k] - mx); sum += r[k]; }
        for (int k = 0; k < 40; k++) r[k] = rbf(r[k] / sum);
    }
    __syncthreads();
    for (int q = 0; q < 40; q++) {
        float a = 0.f;
        for (int k = 0; k < 40; k++) a = fmaf(p[q][k], __bfloat162float(f_qkv[2][k * 4096 + hb + threadIdx.x]), a);
        f_o[q * 4096 + hb + threadIdx.x] = __float2bfloat16_rn(a);
    }
}
__global__ void fb_out(const AuxArgs P, bf16* memn, int s) {
    __shared__ float o[4096]; __shared__ float red[128];
    const int r = blockIdx.x, c = blockIdx.y * 128 + threadIdx.x;
    for (int i = threadIdx.x; i < 4096; i += 128) o[i] = __bfloat162float(f_o[r * 4096 + i]);
    const int row = s * 32 + r - 8;
    float ga = 0.f;
    if (r >= 8) for (int d = threadIdx.x; d < DM_; d += 128) ga += rbf(__bfloat162float(P.x[(size_t)row * DM_ + d]) * __bfloat162float(P.gatew[d]));
    red[threadIdx.x] = ga;
    __syncthreads();
    float a = 0.f;
    for (int k = 0; k < 4096; k++) a = fmaf(o[k], __bfloat162float(P.Wo[(size_t)k * DM_ + c]), a);
    if (r < 8) { memn[r * DM_ + c] = __float2bfloat16_rn(a); return; }
    ga = 0.f; for (int i = 0; i < 128; i++) ga += red[i];
    const float gt = rbf(1.f / (1.f + expf(-rbf(ga)))), og = rbf(1.f - gt);
    P.out[(size_t)row * DM_ + c] = __float2bfloat16_rn(rbf(gt * rbf(a)) + rbf(og * __bfloat162float(g_b[(size_t)row * DM_ + c])));
}

typedef CUresult (*EncodeFn)(CUtensorMap*, CUtensorMapDataType, cuuint32_t, void*, const cuuint64_t*, const cuuint64_t*,
                             const cuuint32_t*, const cuuint32_t*, CUtensorMapInterleave, CUtensorMapSwizzle,
                             CUtensorMapL2promotion, CUtensorMapFloatOOBfill);

extern "C" void kernel_launch(void* const* d_in, const int* in_sizes, int n_in, void* d_out, int out_size) {
    const bf16* x = (const bf16*)d_in[0];
    const bf16* mem0 = (const bf16*)d_in[1];
    const bf16* Wq = (const bf16*)d_in[2];
    const bf16* Wk = (const bf16*)d_in[3];
    const bf16* Wv = (const bf16*)d_in[4];
    const bf16* Wo = (const bf16*)d_in[5];
    const bf16* Bk = (const bf16*)d_in[8];
    const bf16* Bv = (const bf16*)d_in[9];
    const bf16* shk = (const bf16*)d_in[10];
    const bf16* ssmk = (const bf16*)d_in[11];
    const bf16* ssmD = (const bf16*)d_in[12];
    const bf16* gatew = (const bf16*)d_in[13];

    static EncodeFn enc = nullptr;
    static int fast = -1;
    if (fast < 0) {
        void* fn = nullptr; cudaDriverEntryPointQueryResult qr;
        cudaGetDriverEntryPoint("cuTensorMapEncodeTiled", &fn, cudaEnableDefault, &qr);
        enc = (EncodeFn)fn;
        cudaFuncSetAttribute(rec_kernel, cudaFuncAttributeMaxDynamicSharedMemorySize, A_SMEM + 1024);
        cudaFuncSetAttribute(rec_kernel, cudaFuncAttributeNonPortableClusterSizeAllowed, 1);
        cudaFuncSetAttribute(aux_kernel, cudaFuncAttributeMaxDynamicSharedMemorySize, B_SMEM);
        cudaLaunchConfig_t qc = {};
        qc.gridDim = dim3(A_CTAS); qc.blockDim = dim3(A_THREADS); qc.dynamicSmemBytes = A_SMEM + 1024;
        cudaLaunchAttribute qa[1];
        qa[0].id = cudaLaunchAttributeClusterDimension; qa[0].val.clusterDim.x = 16; qa[0].val.clusterDim.y = 1; qa[0].val.clusterDim.z = 1;
        qc.attrs = qa; qc.numAttrs = 1;
        int ncl = 0, nsm = 0, dev = 0;
        cudaGetDevice(&dev);
        cudaDeviceGetAttribute(&nsm, cudaDevAttrMultiProcessorCount, dev);
        if (cudaOccupancyMaxActiveClusters(&ncl, rec_kernel, &qc) != cudaSuccess) { ncl = 0; cudaGetLastError(); }
        fast = (enc != nullptr && ncl >= 7 && nsm >= A_CTAS + NB_CTAS - N_SPARE + 1) ? 1 : 0;
    }
    if (!fast) {
        cudaStream_t fs = cudaStreamPerThread;
        AuxArgs FP = {x, Wo, Bk, Bv, shk, ssmk, ssmD, gatew, (bf16*)d_out};
        bf16* fm; cudaGetSymbolAddress((void**)&fm, f_mem);
        fb_conv<<<DM_, 256, 0, fs>>>(FP);
        for (int s = 0; s < NSEG_; s++) {
            fb_proj<<<dim3(32, 3), 128, 0, fs>>>(x, s == 0 ? mem0 : fm + (s & 1) * 8 * DM_, Wq, Wk, Wv, s);
            fb_attn<<<32, 128, 0, fs>>>();
            fb_out<<<dim3(40, 5), 128, 0, fs>>>(FP, fm + ((s + 1) & 1) * 8 * DM_, s);
        }
        return;
    }
    CUtensorMap tmx;
    {
        cuuint64_t dims[3] = {64, (cuuint64_t)S_, 10};
        cuuint64_t strides[2] = {DM_ * 2, 128};
        cuuint32_t box[3] = {64, 32, 1}, es[3] = {1, 1, 1};
        enc(&tmx, CU_TENSOR_MAP_DATA_TYPE_BFLOAT16, 3, (void*)x, dims, strides, box, es, CU_TENSOR_MAP_INTERLEAVE_NONE,
            CU_TENSOR_MAP_SWIZZLE_128B, CU_TENSOR_MAP_L2_PROMOTION_L2_256B, CU_TENSOR_MAP_FLOAT_OOB_FILL_NONE);
    }
    cudaStream_t st = cudaStreamPerThread;
    AuxArgs P = {x, Wo, Bk, Bv, shk, ssmk, ssmD, gatew, (bf16*)d_out};
    {
        cudaLaunchConfig_t ca = {};
        ca.gridDim = dim3(A_CTAS); ca.blockDim = dim3(A_THREADS); ca.dynamicSmemBytes = A_SMEM + 1024; ca.stream = st;
        cudaLaunchAttribute aa[1];
        aa[0].id = cudaLaunchAttributeClusterDimension; aa[0].val.clusterDim.x = 16; aa[0].val.clusterDim.y = 1; aa[0].val.clusterDim.z = 1;
        ca.attrs = aa; ca.numAttrs = 1;
        cudaLaunchKernelEx(&ca, rec_kernel, tmx, mem0, Wq, Wk, Wv, Wo, P);
    }
    cudaLaunchConfig_t cfg = {};
    cfg.gridDim = dim3(NB_CTAS - N_SPARE + 1);
    cfg.blockDim = dim3(B_THREADS); cfg.dynamicSmemBytes = B_SMEM; cfg.stream = st;
    cudaLaunchAttribute at[1];
    at[0].id = cudaLaunchAttributeProgrammaticStreamSerialization; at[0].val.programmaticStreamSerializationAllowed = 1;
    cfg.attrs = at; cfg.numAttrs = 1;
    cudaLaunchKernelEx(&cfg, aux_kernel, P);
}
```

```cpp
#include <cuda_runtime.h>
#include <cuda_bf16.h>
#include <cuda.h>
#include <stdint.h>

typedef __nv_bfloat16 bf16;

constexpr int S_ = 2048, DM_ = 640, NH_ = 32, NSEG_ = 64;
constexpr int NKG_ = 7, NCR_ = 5, NB_CTAS = NKG_ * NCR_;

#define DELAY_X 250
#define LOOKW 20
#define START_DELAY 10000
#define SPIN_LIMIT (1 << 13)
#define SPIN_FAIL(guard, code) (((++guard) & 1023) == 0 && (guard >= SPIN_LIMIT || *(volatile unsigned*)&g_misc[2] != 0) && ((g_misc[2] = (code)), true))

__device__ uint2 g_X[4][40 * 7 * 32];
__device__ uint4 g_ox[(size_t)NSEG_ * NH_ * 512];
__device__ float g_part[(size_t)NKG_ * S_ * DM_];
__device__ bf16 g_b[(size_t)S_ * DM_];
__device__ float g_gate[S_];
__device__ unsigned g_oxcnt[NSEG_ * 8];
__device__ unsigned g_pcnt[NSEG_ * 8];
__device__ unsigned g_misc[4];
#define CAL(b, i) do {} while (0)

__device__ __forceinline__ uint32_t smem_u32(const void* p) { return (uint32_t)__cvta_generic_to_shared(p); }
__device__ __forceinline__ void mbar_init(uint32_t mb, int cnt) { asm volatile("mbarrier.init.shared.b64 [%0], %1;" ::"r"(mb), "r"(cnt)); }
__device__ __forceinline__ void mbar_expect(uint32_t mb, int bytes) { asm volatile("mbarrier.arrive.expect_tx.shared.b64 _, [%0], %1;" ::"r"(mb), "r"(bytes) : "memory"); }
__device__ __forceinline__ void mbar_arrive(uint32_t mb) { asm volatile("mbarrier.arrive.shared.b64 _, [%0];" ::"r"(mb) : "memory"); }
__device__ __forceinline__ bool mbar_try(uint32_t mb, int parity) {
    uint32_t ok;
    asm volatile("{ .reg .pred p; mbarrier.try_wait.parity.shared.b64 p, [%1], %2; selp.u32 %0, 1, 0, p; }" : "=r"(ok) : "r"(mb), "r"(parity) : "memory");
    return ok;
}
__device__ __forceinline__ void mbar_wait(uint32_t mb, int parity) {
    int guard = 0;
    while (!mbar_try(mb, parity)) { if (SPIN_FAIL(guard, 1)) break; }
}
__device__ __forceinline__ void mbar_wait_u(uint32_t mb, int parity) {
    asm volatile("{ .reg .pred p; .reg .u32 c; mov.u32 c, 0;\n"
                 "WL%=: mbarrier.try_wait.parity.shared.b64 p, [%0], %1;\n"
                 "@p bra.uni WD%=;\n"
                 "add.u32 c, c, 1; setp.lt.u32 p, c, 16384;\n"
                 "@p bra.uni WL%=;\n"
                 "WD%=: }" ::"r"(mb), "r"(parity) : "memory");
}
__device__ __forceinline__ uint32_t movm(uint32_t a) { uint32_t d; asm volatile("movmatrix.sync.aligned.m8n8.trans.b16 %0, %1;" : "=r"(d) : "r"(a)); return d; }
__device__ __forceinline__ float ex2(float x) { float y; asm("ex2.approx.ftz.f32 %0, %1;" : "=f"(y) : "f"(x)); return y; }
__device__ __forceinline__ float rcp(float x) { float y; asm("rcp.approx.ftz.f32 %0, %1;" : "=f"(y) : "f"(x)); return y; }
__device__ __forceinline__ uint32_t mapa(uint32_t a, uint32_t r) { uint32_t o; asm volatile("mapa.shared::cluster.u32 %0, %1, %2;" : "=r"(o) : "r"(a), "r"(r)); return o; }
__device__ __forceinline__ uint4 ld_poll16(const void* p) { uint4 v; asm volatile("ld.relaxed.gpu.global.v4.u32 {%0,%1,%2,%3}, [%4];" : "=r"(v.x), "=r"(v.y), "=r"(v.z), "=r"(v.w) : "l"(p) : "memory"); return v; }
__device__ __forceinline__ void st_rel16(void* p, uint4 v) { asm volatile("st.relaxed.gpu.global.v4.u32 [%0], {%1,%2,%3,%4};" ::"l"(p), "r"(v.x), "r"(v.y), "r"(v.z), "r"(v.w) : "memory"); }
__device__ __forceinline__ void st_rel4(void* p, uint32_t v) { asm volatile("st.relaxed.gpu.global.u32 [%0], %1;" ::"l"(p), "r"(v) : "memory"); }
__device__ __forceinline__ unsigned ld_acq(const unsigned* p) { unsigned v; asm volatile("ld.acquire.gpu.global.u32 %0, [%1];" : "=r"(v) : "l"(p) : "memory"); return v; }
__device__ __forceinline__ void red_rel(unsigned* p, unsigned v) { asm volatile("red.release.gpu.global.add.u32 [%0], %1;" ::"l"(p), "r"(v) : "memory"); }
__device__ __forceinline__ void bar_sync(int id, int n) { asm volatile("bar.sync %0, %1;" ::"r"(id), "r"(n) : "memory"); }
__device__ __forceinline__ void st_async8(uint32_t dst, uint32_t a, uint32_t b, uint32_t mb) {
    asm volatile("st.async.weak.shared::cluster.mbarrier::complete_tx::bytes.v2.b32 [%0], {%1,%2}, [%3];" ::"r"(dst), "r"(a), "r"(b), "r"(mb) : "memory");
}
__device__ __forceinline__ void st_async16(uint32_t dst, uint32_t a, uint32_t b, uint32_t c, uint32_t d, uint32_t mb) {
    asm volatile("st.async.weak.shared::cluster.mbarrier::complete_tx::bytes.v4.b32 [%0], {%1,%2,%3,%4}, [%5];" ::"r"(dst), "r"(a), "r"(b), "r"(c), "r"(d), "r"(mb) : "memory");
}
__device__ __forceinline__ uint2 lds64(uint32_t a) { uint2 v; asm volatile("ld.shared.v2.u32 {%0,%1}, [%2];" : "=r"(v.x), "=r"(v.y) : "r"(a) : "memory"); return v; }
__device__ __forceinline__ uint2 ld_poll8(const void* p) { uint2 v; asm volatile("ld.relaxed.gpu.global.v2.u32 {%0,%1}, [%2];" : "=r"(v.x), "=r"(v.y) : "l"(p) : "memory"); return v; }
__device__ __forceinline__ void bulk_s2s(uint32_t dst, uint32_t src, uint32_t bytes, uint32_t mb) {
    asm volatile("cp.async.bulk.shared::cluster.shared::cta.mbarrier::complete_tx::bytes [%0], [%1], %2, [%3];" ::"r"(dst), "r"(src), "r"(bytes), "r"(mb) : "memory");
}
__device__ __forceinline__ void bulk_g2s(uint32_t dst, const void* src, uint32_t bytes, uint32_t mb) {
    asm volatile("cp.async.bulk.shared::cluster.global.mbarrier::complete_tx::bytes [%0], [%1], %2, [%3];" ::"r"(dst), "l"(src), "r"(bytes), "r"(mb) : "memory");
}
__device__ __forceinline__ void tma3d(uint32_t dst, const CUtensorMap* tm, int c0, int c1, int c2, uint32_t mb) {
    asm volatile("cp.async.bulk.tensor.3d.shared::cluster.global.mbarrier::complete_tx::bytes [%0], [%1, {%3, %4, %5}], [%2];"
                 ::"r"(dst), "l"((uint64_t)tm), "r"(mb), "r"(c0), "r"(c1), "r"(c2) : "memory");
}
__device__ __forceinline__ void tma3d_mc(uint32_t dst, const CUtensorMap* tm, int c0, int c1, int c2, uint32_t mb, uint16_t mask) {
    asm volatile("cp.async.bulk.tensor.3d.shared::cluster.global.mbarrier::complete_tx::bytes.multicast::cluster [%0], [%1, {%3, %4, %5}], [%2], %6;"
                 ::"r"(dst), "l"((uint64_t)tm), "r"(mb), "r"(c0), "r"(c1), "r"(c2), "h"(mask) : "memory");
}
__device__ __forceinline__ void st_rel8(void* p, uint32_t a, uint32_t b) { asm volatile("st.relaxed.gpu.global.v2.u32 [%0], {%1,%2};" ::"l"(p), "r"(a), "r"(b) : "memory"); }
__device__ __forceinline__ void fence_async_smem() { asm volatile("fence.proxy.async.shared::cta;" ::: "memory"); }
__device__ __forceinline__ void fence_async_all() { asm volatile("fence.proxy.async;" ::: "memory"); }
__device__ __forceinline__ void cp_async16(uint32_t dst, const void* src) { asm volatile("cp.async.cg.shared.global [%0], [%1], 16;" ::"r"(dst), "l"(src) : "memory"); }
__device__ __forceinline__ void cluster_sync() { asm volatile("barrier.cluster.arrive.aligned; barrier.cluster.wait.aligned;" ::: "memory"); }
__device__ __forceinline__ int clk() { int c; asm volatile("mov.u32 %0, %%clock;" : "=r"(c)); return c; }

__device__ __forceinline__ void ldsm4(uint32_t* r, uint32_t a) { asm volatile("ldmatrix.sync.aligned.m8n8.x4.shared.b16 {%0,%1,%2,%3}, [%4];" : "=r"(r[0]), "=r"(r[1]), "=r"(r[2]), "=r"(r[3]) : "r"(a) : "memory"); }
__device__ __forceinline__ void ldsm2(uint32_t* r, uint32_t a) { asm volatile("ldmatrix.sync.aligned.m8n8.x2.shared.b16 {%0,%1}, [%2];" : "=r"(r[0]), "=r"(r[1]) : "r"(a) : "memory"); }
__device__ __forceinline__ void ldsm4t(uint32_t* r, uint32_t a) { asm volatile("ldmatrix.sync.aligned.m8n8.x4.trans.shared.b16 {%0,%1,%2,%3}, [%4];" : "=r"(r[0]), "=r"(r[1]), "=r"(r[2]), "=r"(r[3]) : "r"(a) : "memory"); }
__device__ __forceinline__ void ldsm2t(uint32_t* r, uint32_t a) { asm volatile("ldmatrix.sync.aligned.m8n8.x2.trans.shared.b16 {%0,%1}, [%2];" : "=r"(r[0]), "=r"(r[1]) : "r"(a) : "memory"); }
__device__ __forceinline__ void stsm4t(uint32_t a, uint32_t r0, uint32_t r1, uint32_t r2, uint32_t r3) {
    asm volatile("stmatrix.sync.aligned.m8n8.x4.trans.shared.b16 [%0], {%1,%2,%3,%4};" ::"r"(a), "r"(r0), "r"(r1), "r"(r2), "r"(r3) : "memory");
}
__device__ __forceinline__ uint4 lds128(uint32_t a) { uint4 v; asm volatile("ld.shared.v4.u32 {%0,%1,%2,%3}, [%4];" : "=r"(v.x), "=r"(v.y), "=r"(v.z), "=r"(v.w) : "r"(a) : "memory"); return v; }
__device__ __forceinline__ float2 lds64f(uint32_t a) { float2 v; asm volatile("ld.shared.v2.f32 {%0,%1}, [%2];" : "=f"(v.x), "=f"(v.y) : "r"(a) : "memory"); return v; }
__device__ __forceinline__ float lds32f(uint32_t a) { float v; asm volatile("ld.shared.f32 %0, [%1];" : "=f"(v) : "r"(a) : "memory"); return v; }
__device__ __forceinline__ uint32_t lds32(uint32_t a) { uint32_t v; asm volatile("ld.shared.u32 %0, [%1];" : "=r"(v) : "r"(a) : "memory"); return v; }
__device__ __forceinline__ void sts128(uint32_t a, uint4 v) { asm volatile("st.shared.v4.u32 [%0], {%1,%2,%3,%4};" ::"r"(a), "r"(v.x), "r"(v.y), "r"(v.z), "r"(v.w) : "memory"); }
__device__ __forceinline__ void sts128f(uint32_t a, float x, float y, float z, float w) { asm volatile("st.shared.v4.f32 [%0], {%1,%2,%3,%4};" ::"r"(a), "f"(x), "f"(y), "f"(z), "f"(w) : "memory"); }
__device__ __forceinline__ void sts64f(uint32_t a, float x, float y) { asm volatile("st.shared.v2.f32 [%0], {%1,%2};" ::"r"(a), "f"(x), "f"(y) : "memory"); }
__device__ __forceinline__ void sts64(uint32_t a, uint32_t x, uint32_t y) { asm volatile("st.shared.v2.u32 [%0], {%1,%2};" ::"r"(a), "r"(x), "r"(y) : "memory"); }
__device__ __forceinline__ void sts32f(uint32_t a, float x) { asm volatile("st.shared.f32 [%0], %1;" ::"r"(a), "f"(x) : "memory"); }

__device__ __forceinline__ void mma16(float* d, const uint32_t* a, uint32_t b0, uint32_t b1) {
    asm volatile("mma.sync.aligned.m16n8k16.row.col.f32.bf16.bf16.f32 {%0,%1,%2,%3}, {%4,%5,%6,%7}, {%8,%9}, {%0,%1,%2,%3};"
                 : "+f"(d[0]), "+f"(d[1]), "+f"(d[2]), "+f"(d[3]) : "r"(a[0]), "r"(a[1]), "r"(a[2]), "r"(a[3]), "r"(b0), "r"(b1));
}
__device__ __forceinline__ void mma16r(float* d, uint32_t a0, uint32_t a1, uint32_t a2, uint32_t a3, uint32_t b0, uint32_t b1) {
    asm volatile("mma.sync.aligned.m16n8k16.row.col.f32.bf16.bf16.f32 {%0,%1,%2,%3}, {%4,%5,%6,%7}, {%8,%9}, {%0,%1,%2,%3};"
                 : "+f"(d[0]), "+f"(d[1]), "+f"(d[2]), "+f"(d[3]) : "r"(a0), "r"(a1), "r"(a2), "r"(a3), "r"(b0), "r"(b1));
}
__device__ __forceinline__ void mma8(float* d, uint32_t a0, uint32_t a1, uint32_t b0) {
    asm volatile("mma.sync.aligned.m16n8k8.row.col.f32.bf16.bf16.f32 {%0,%1,%2,%3}, {%4,%5}, {%6}, {%0,%1,%2,%3};"
                 : "+f"(d[0]), "+f"(d[1]), "+f"(d[2]), "+f"(d[3]) : "r"(a0), "r"(a1), "r"(b0));
}
__device__ __forceinline__ void wgmma_n32(float* d, const uint32_t* a, uint32_t desc_lo, int sc) {
    asm volatile("{ .reg .pred p; .reg .b64 dd; setp.ne.b32 p, %21, 0; mov.b64 dd, {%20, 0x40000040};\n"
                 "wgmma.mma_async.sync.aligned.m64n32k16.f32.bf16.bf16 {%0,%1,%2,%3,%4,%5,%6,%7,%8,%9,%10,%11,%12,%13,%14,%15}, {%16,%17,%18,%19}, dd, p, 1, 1, 0; }\n"
                 : "+f"(d[0]), "+f"(d[1]), "+f"(d[2]), "+f"(d[3]), "+f"(d[4]), "+f"(d[5]), "+f"(d[6]), "+f"(d[7]),
                   "+f"(d[8]), "+f"(d[9]), "+f"(d[10]), "+f"(d[11]), "+f"(d[12]), "+f"(d[13]), "+f"(d[14]), "+f"(d[15])
                 : "r"(a[0]), "r"(a[1]), "r"(a[2]), "r"(a[3]), "r"(desc_lo), "r"(sc));
}
#define WG_FENCE() asm volatile("wgmma.fence.sync.aligned;" ::: "memory")
#define WG_COMMIT() asm volatile("wgmma.commit_group.sync.aligned;" ::: "memory")
#define WG_WAIT0() asm volatile("wgmma.wait_group.sync.aligned 0;" ::: "memory")
__device__ __forceinline__ uint32_t desc_sw128(uint32_t saddr) { return ((saddr & 0x3FFFF) >> 4) | (1u << 16); }
__device__ __forceinline__ uint32_t pack2(float lo, float hi) { __nv_bfloat162 h = __floats2bfloat162_rn(lo, hi); return *(uint32_t*)&h; }
__device__ __forceinline__ float bflo(uint32_t u) { return __uint_as_float(u << 16); }
__device__ __forceinline__ float bfhi(uint32_t u) { return __uint_as_float(u & 0xffff0000u); }
__device__ __forceinline__ float rbf(float x) { return __uint_as_float(pack2(0.f, x)); }
__device__ __forceinline__ uint32_t nzw(uint32_t u) { return u == 0 ? 0x80008000u : u; }
__device__ __forceinline__ uint32_t min4(uint4 v) { return min(min(v.x, v.y), min(v.z, v.w)); }
__device__ __forceinline__ void mbar_arrive_if(uint32_t mb, uint32_t c) {
    asm volatile("{ .reg .pred p; setp.ne.u32 p, %1, 0; @p mbarrier.arrive.shared.b64 _, [%0]; }" ::"r"(mb), "r"(c) : "memory");
}
__device__ __forceinline__ int eperm(int p) { return (p & ~15) + 2 * (p & 7) + ((p >> 3) & 1); }

constexpr int U_STRIDE = 136 * 48;
constexpr int KR_STRIDE = 2080 * 2 * 2;
constexpr int B_U_OFF = 0, B_KR_OFF = 8 * U_STRIDE, B_CONV_END = B_KR_OFF + 8 * KR_STRIDE;
constexpr int B_OX_STAGES = 3, B_OX_BYTES = 40960;
constexpr int B_BAR_OFF = B_OX_STAGES * B_OX_BYTES;
constexpr int B_SMEM = B_BAR_OFF + 128;

constexpr int B_THREADS = 384;

struct AuxArgs { const bf16 *x, *Wo, *Bk, *Bv, *shk, *ssmk, *ssmD, *gatew; bf16* out; };
constexpr int MBB_FULL = B_BAR_OFF, MBB_EMPTY = B_BAR_OFF + 24, MBB_ST = B_BAR_OFF + 48, MBB_GO = B_BAR_OFF + 80, MBB_FLAG = B_BAR_OFF + 96;

__device__ __forceinline__ void aux_init(uint32_t sb) {
    for (int i = 0; i < B_OX_STAGES; i++) { mbar_init(sb + MBB_FULL + 8 * i, 1); mbar_init(sb + MBB_EMPTY + 8 * i, 8); }
    for (int i = 0; i < 4; i++) mbar_init(sb + MBB_ST + 8 * i, 8);
    mbar_init(sb + MBB_GO, 8);
    fence_async_smem();
}
__device__ __forceinline__ bool mbar_test(uint32_t mb, int parity) {
    uint32_t ok;
    asm volatile("{ .reg .pred p; mbarrier.test_wait.parity.shared.b64 p, [%1], %2; selp.u32 %0, 1, 0, p; }" : "=r"(ok) : "r"(mb), "r"(parity) : "memory");
    return ok;
}
__device__ __forceinline__ bool aux_quiet(int p) { return p >= 4 && p < 16 && ((p - 4) & 2) == 0; }
__device__ __forceinline__ int aux_ord(int p) { return p < 4 ? p : (p < 16 ? 4 + ((p - 4) >> 2) * 2 + (p & 1) : p - 6); }
__device__ __forceinline__ int aux_vid(int p) {
    if (aux_quiet(p)) { const int qi = ((p - 4) >> 2) * 2 + (p & 1); return qi < 5 ? 30 + qi : 25; }
    const int o = aux_ord(p); return o < 25 ? o : o + 1;
}
constexpr unsigned AUX_EXITS = NB_CTAS + 29 * 3 + 1;
__device__ __forceinline__ bool aux_exit_last() {
    unsigned old; asm volatile("atom.acq_rel.gpu.global.add.u32 %0, [%1], 1;" : "=r"(old) : "l"(&g_misc[1]) : "memory");
    return old == AUX_EXITS - 1;
}
__device__ __forceinline__ void aux_reset(int i0, int step) {
    for (int i = i0; i < NSEG_ * 8; i += step) { g_oxcnt[i] = 0; g_pcnt[i] = 0; }
    if (i0 == 0) { g_misc[0] = 0; g_misc[1] = 0; }
}
__device__ __forceinline__ void aux_final(const AuxArgs& P, int p, int fw) {
    const int vid = aux_vid(p), kg = vid / NCR_, cr = vid % NCR_, nf = cr == 0 ? 5 : 6;
    const int lane = threadIdx.x & 31, c = cr * 128 + lane * 4;
    const int r0 = vid == 25 ? 30 : kg + nf * fw, rstep = vid == 25 ? 1 : 3 * nf, rend = (cr == 0 && vid != 25) ? 30 : 32;
    if (lane == 0) { int guard = 0; while (ld_acq(&g_misc[0]) < (unsigned)(NB_CTAS + 1)) { if (++guard > (1 << 20)) break; __nanosleep(500); } }
    __syncwarp();
    int ready = 0;
#pragma unroll 1
    for (int n = 0; n < NSEG_; n++) {
        if (n >= ready) {
            int guard = 0;
            while (true) {
                const bool ok = n + lane < NSEG_ && ld_acq(&g_pcnt[(n + lane) * 8 + cr]) >= (unsigned)NKG_;
                const unsigned m = __ballot_sync(~0u, ok);
                ready = n + (m == ~0u ? 32 : __ffs(~m) - 1);
                if (ready > n) break;
                if (++guard > (1 << 18)) { g_misc[2] = 6; ready = NSEG_; break; }
                __nanosleep(100);
            }
            __syncwarp();
        }
#pragma unroll 1
        for (int r = r0; r < rend; r += rstep) {
            const int row = n * 32 + r;
            float4 v[NKG_];
#pragma unroll
            for (int k = 0; k < NKG_; k++) v[k] = __ldcg((const float4*)(g_part + ((size_t)k * S_ + row) * DM_ + c));
            const float gt = __ldcg(&g_gate[row]), og = rbf(1.f - gt);
            const uint2 bv = __ldcg((const uint2*)(g_b + (size_t)row * DM_ + c));
            float4 a = v[0];
#pragma unroll
            for (int k = 1; k < NKG_; k++) { a.x += v[k].x; a.y += v[k].y; a.z += v[k].z; a.w += v[k].w; }
            uint2 o;
            o.x = pack2(rbf(gt * rbf(a.x)) + rbf(og * bflo(bv.x)), rbf(gt * rbf(a.y)) + rbf(og * bfhi(bv.x)));
            o.y = pack2(rbf(gt * rbf(a.z)) + rbf(og * bflo(bv.y)), rbf(gt * rbf(a.w)) + rbf(og * bfhi(bv.y)));
            *(uint2*)(P.out + (size_t)row * DM_ + c) = o;
        }
    }
    bool last = false;
    if (lane == 0) last = aux_exit_last();
    if (__shfl_sync(~0u, last, 0)) aux_reset(lane, 32);
}
__device__ __forceinline__ void aux_control(uint32_t sb, int p) {
    const int vid = aux_vid(p), kg = vid / NCR_, cr = vid % NCR_;
    const int h0 = kg < 4 ? kg * 5 : 20 + (kg - 4) * 4, nh = kg < 4 ? 5 : 4;
    { int guard = 0; while (!mbar_try(sb + MBB_GO, 0)) { if (++guard > (1 << 22)) break; } }
    red_rel(&g_misc[0], 1);
    if (p == NB_CTAS) return;
    int nl = 0, nr = 0, guard = 0;
    while (nr < NSEG_) {
        bool did = false;
        if (nl < NSEG_ && nl < nr + 4) {
            const int st = nl % B_OX_STAGES;
            if ((nl < B_OX_STAGES || mbar_test(sb + MBB_EMPTY + 8 * st, (nl / B_OX_STAGES - 1) & 1)) &&
                ld_acq(&g_oxcnt[nl * 8 + kg]) >= (unsigned)(2 * nh)) {
                fence_async_all();
                mbar_expect(sb + MBB_FULL + 8 * st, nh * 8192);
                bulk_g2s(sb + st * B_OX_BYTES, g_ox + (size_t)(nl * NH_ + h0) * 512, nh * 8192, sb + MBB_FULL + 8 * st);
                nl++; did = true;
            }
        }
        if (nr < nl && mbar_test(sb + MBB_ST + 8 * (nr & 3), (nr >> 2) & 1)) { red_rel(&g_pcnt[nr * 8 + cr], 1); nr++; did = true; }
        if (did) guard = 0;
        else { if (++guard > (1 << 17)) { g_misc[2] = 4; break; } __nanosleep(100); }
    }
    if (aux_exit_last()) aux_reset(0, 1);
}
__device__ __forceinline__ void aux_compute(const AuxArgs& P, unsigned char* smem, uint32_t sb, int cta, int warp) {
    const bf16* __restrict__ x = P.x; const bf16* __restrict__ Wo = P.Wo; const bf16* __restrict__ Bk = P.Bk; const bf16* __restrict__ Bv = P.Bv;
    const bf16* __restrict__ shk = P.shk; const bf16* __restrict__ ssmk = P.ssmk; const bf16* __restrict__ ssmD = P.ssmD;
    const bf16* __restrict__ gatew = P.gatew; bf16* __restrict__ out = P.out;
    const int tid = threadIdx.x, lane = tid & 31;
    const int g = lane >> 2, t = lane & 3;
    const int vid = aux_vid(cta), kg = vid / NCR_, cr = vid % NCR_;
    const bool quiet = aux_quiet(cta);
    const int ord = aux_ord(cta);
    const int h0 = kg < 4 ? kg * 5 : 20 + (kg - 4) * 4, nh = kg < 4 ? 5 : 4;
    const uint32_t mb_full = sb + MBB_FULL, mb_empty = sb + MBB_EMPTY, mb_st = sb + MBB_ST, mb_go = sb + MBB_GO;
    CAL(112 + cta, 0);
    if (cta == NB_CTAS) { const long long t0 = clock64(); while (clock64() - t0 < START_DELAY) __nanosleep(200); }
    else if (!quiet) {
        { const long long t0 = clock64(); while (clock64() - t0 < START_DELAY) __nanosleep(200); }
        uint32_t wv[10];
#pragma unroll
        for (int i = 0; i < 10; i++) wv[i] = __ldg((const uint32_t*)gatew + lane + 32 * i);
        uint32_t xv[9][10];
#pragma unroll
        for (int j = 0; j < 9; j++) {
            const int r = min(ord * 8 + warp + j * 232, S_ - 1);
#pragma unroll
            for (int i = 0; i < 10; i++) xv[j][i] = __ldg((const uint32_t*)(x + (size_t)r * DM_) + lane + 32 * i);
        }
#pragma unroll
        for (int j = 0; j < 9; j++) {
            const int r = ord * 8 + warp + j * 232;
            float acc = 0.f;
#pragma unroll
            for (int i = 0; i < 10; i++) acc += rbf(bflo(xv[j][i]) * bflo(wv[i])) + rbf(bfhi(xv[j][i]) * bfhi(wv[i]));
#pragma unroll
            for (int o = 16; o; o >>= 1) acc += __shfl_xor_sync(~0u, acc, o);
            if (lane == 0 && r < S_) g_gate[r] = rbf(1.f / (1.f + __expf(-rbf(acc))));
        }
    }

    int item0, nitem;
    if (cta >= 16) { item0 = 3 * (cta - 16); nitem = 3; }
    else { item0 = 60 + 2 * ord; nitem = quiet ? 0 : 2; }
    for (int item = item0; item < item0 + nitem; item++) {
        const int c0 = item * 8;
        bar_sync(1, 256);
        for (int i = tid; i < 8 * 24; i += 256) sts128(sb + B_U_OFF + (i / 24) * U_STRIDE + (i % 24) * 16, make_uint4(0, 0, 0, 0));
        {
            const uint32_t krb = sb + B_KR_OFF + warp * KR_STRIDE;
            const bf16* kp = ssmk + (size_t)(c0 + warp) * S_;
            uint4 v[8]; uint32_t pv[8];
#pragma unroll
            for (int j = 0; j < 8; j++) {
                const int i = lane + 32 * j;
                v[j] = __ldg((const uint4*)kp + i);
                pv[j] = i > 0 ? __ldg((const uint32_t*)kp + 4 * i - 1) : 0u;
            }
#pragma unroll
            for (int j = 0; j < 8; j++) {
                const int i = lane + 32 * j;
                sts128(krb + (2040 - 8 * i) * 2, make_uint4(__byte_perm(v[j].w, 0, 0x1032), __byte_perm(v[j].z, 0, 0x1032),
                                                            __byte_perm(v[j].y, 0, 0x1032), __byte_perm(v[j].x, 0, 0x1032)));
                sts128(krb + 4160 + (2040 - 8 * i) * 2, make_uint4(__byte_perm(v[j].w, v[j].z, 0x7610), __byte_perm(v[j].z, v[j].y, 0x7610),
                                                                   __byte_perm(v[j].y, v[j].x, 0x7610), __byte_perm(v[j].x, pv[j], 0x7610)));
            }
            if (lane < 4) { sts128(krb + 4096 + lane * 16, make_uint4(0, 0, 0, 0)); sts128(krb + 4160 + 4096 + lane * 16, make_uint4(0, 0, 0, 0)); }
        }
        {
            float sh[8][4];
#pragma unroll
            for (int c = 0; c < 8; c++) {
                uint2 v = __ldg((const uint2*)(shk + (c0 + c) * 4));
                sh[c][0] = bflo(v.x); sh[c][1] = bfhi(v.x); sh[c][2] = bflo(v.y); sh[c][3] = bfhi(v.y);
            }
            const int t0 = tid * 8;
            uint4 kr[11], vr[8];
#pragma unroll
            for (int i = 0; i < 11; i++) { int r = t0 - 3 + i; kr[i] = r >= 0 ? __ldg((const uint4*)(Bk + (size_t)r * DM_ + c0)) : make_uint4(0, 0, 0, 0); }
#pragma unroll
            for (int i = 0; i < 8; i++) vr[i] = __ldg((const uint4*)(Bv + (size_t)(t0 + i) * DM_ + c0));
#pragma unroll
            for (int c = 0; c < 8; c++) {
                float res[8];
#pragma unroll
                for (int i = 0; i < 8; i++) {
                    float a = 0.f;
#pragma unroll
                    for (int tt = 0; tt < 4; tt++) {
                        uint32_t wd = ((const uint32_t*)&kr[i + tt])[c >> 1];
                        float kv_ = (c & 1) ? bfhi(wd) : bflo(wd);
                        a = rbf(a + rbf(kv_ * sh[c][3 - tt]));
                    }
                    uint32_t wd = ((const uint32_t*)&vr[i])[c >> 1];
                    res[i] = a * ((c & 1) ? bfhi(wd) : bflo(wd));
                }
                uint4 o = make_uint4(pack2(res[0], res[1]), pack2(res[2], res[3]), pack2(res[4], res[5]), pack2(res[6], res[7]));
                sts128(sb + B_U_OFF + c * U_STRIDE + (8 + (tid >> 1)) * 48 + (tid & 1) * 16, o);
            }
        }
        bar_sync(1, 256);
        {
            float acc[16][4];
#pragma unroll
            for (int i = 0; i < 64; i++) ((float*)acc)[i] = 0.f;
            const uint32_t kb = sb + B_KR_OFF + warp * KR_STRIDE + ((g & 1) ? (2047 - g + 2 * t) * 2 : 4160 + (2046 - g + 2 * t) * 2);
            const uint32_t ub = sb + B_U_OFF + warp * U_STRIDE + (8 + (lane & 7) + (lane >> 4) * 8) * 48 + ((lane >> 3) & 1) * 16;
#pragma unroll 1
            for (int r = 0; r < 8; r++) {
                uint32_t pa[16][3];
#pragma unroll
                for (int m = 0; m < 16; m++) {
                    const uint32_t a = kb - (16 * (r + 8 * m)) * 2;
                    pa[m][0] = lds32(a + 16); pa[m][1] = lds32(a); pa[m][2] = lds32(a - 16);
                }
#pragma unroll
                for (int d = 0; d < 16; d += 2) {
                    uint32_t b[4];
                    ldsm4(b, ub + (8 * d - r) * 48);
#pragma unroll
                    for (int m = 0; m < 16 - d; m++) mma16r(acc[m + d], pa[m][1], pa[m][2], pa[m][0], pa[m][1], b[0], b[1]);
#pragma unroll
                    for (int m = 0; m < 15 - d; m++) mma16r(acc[m + d + 1], pa[m][1], pa[m][2], pa[m][0], pa[m][1], b[2], b[3]);
                }
            }
            __syncwarp();
            const float Dv = __bfloat162float(ssmD[c0 + warp]);
            bf16* u = (bf16*)(smem + B_U_OFF + warp * U_STRIDE) + 8 * 24;
#pragma unroll
            for (int i = 0; i < 16; i++) {
#pragma unroll
                for (int q = 0; q < 4; q++) {
                    const int idx = (8 * i + 2 * t + (q & 1)) * 24 + g + (q >> 1) * 8;
                    const float kvv = __bfloat162float(u[idx]);
                    u[idx] = __float2bfloat16_rn(rbf(acc[i][q]) + rbf(kvv * Dv));
                }
            }
        }
        uint4 xv[8];
#pragma unroll
        for (int j = 0; j < 8; j++) xv[j] = __ldg((const uint4*)(x + (size_t)(tid + 256 * j) * DM_ + c0));
        bar_sync(1, 256);
#pragma unroll
        for (int j = 0; j < 8; j++) {
            const int r = tid + 256 * j;
            uint32_t o[4];
            const bf16* u = (const bf16*)(smem + B_U_OFF) + (8 + (r >> 4)) * 24 + (r & 15);
#pragma unroll
            for (int c = 0; c < 4; c++) {
                uint32_t wd = ((const uint32_t*)&xv[j])[c];
                o[c] = pack2(bflo(wd) * __bfloat162float(u[(2 * c) * (U_STRIDE / 2)]), bfhi(wd) * __bfloat162float(u[(2 * c + 1) * (U_STRIDE / 2)]));
            }
            *(uint4*)(g_b + (size_t)r * DM_ + c0) = make_uint4(o[0], o[1], o[2], o[3]);
        }
    }
    fence_async_smem();
    __syncwarp();
    if (lane == 0) mbar_arrive(mb_go);
    CAL(112 + cta, 1);
    if (cta == NB_CTAS) return;

    const int wg = warp >> 2, w = warp & 3;
    const int col = cr * 128 + wg * 64 + 16 * w + 2 * g;
    uint32_t A[40][4];
#pragma unroll
    for (int ks = 0; ks < 40; ks++) {
        const int hh = ks >> 3;
        uint32_t r[4] = {0, 0, 0, 0};
        if (hh < nh) {
#pragma unroll
            for (int i = 0; i < 4; i++) {
                const int p = (ks & 7) * 16 + 2 * t + (i & 1) + (i >> 1) * 8;
                r[i] = __ldg((const uint32_t*)(Wo + (size_t)((h0 + hh) * 128 + eperm(p)) * DM_ + col));
            }
        }
        A[ks][0] = __byte_perm(r[0], r[1], 0x5410); A[ks][1] = __byte_perm(r[0], r[1], 0x7632);
        A[ks][2] = __byte_perm(r[2], r[3], 0x5410); A[ks][3] = __byte_perm(r[2], r[3], 0x7632);
    }
    CAL(112 + cta, 2);
#pragma unroll 1
    for (int n = 0; n < NSEG_; n++) {
        const int st = n % B_OX_STAGES;
        { int guard = 0; while (!mbar_try(mb_full + 8 * st, (n / B_OX_STAGES) & 1)) { if (++guard > (1 << 20)) break; } }
        __syncwarp();
        float acc[16];
        const uint32_t d0 = __shfl_sync(0xffffffffu, desc_sw128(sb + st * B_OX_BYTES), 0);
        WG_FENCE();
#pragma unroll
        for (int ks = 0; ks < 32; ks++) wgmma_n32(acc, A[ks], d0 + (((ks >> 2) * 4096 + (ks & 3) * 32) >> 4), ks > 0);
        if (nh == 5) {
#pragma unroll
            for (int ks = 32; ks < 40; ks++) wgmma_n32(acc, A[ks], d0 + (((ks >> 2) * 4096 + (ks & 3) * 32) >> 4), 1);
        }
        WG_COMMIT();
        WG_WAIT0();
        if (lane == 0) mbar_arrive(mb_empty + 8 * st);
        float* pp = g_part + ((size_t)kg * S_ + n * 32) * DM_ + col;
#pragma unroll
        for (int j = 0; j < 4; j++) {
            *(float2*)(pp + (size_t)(8 * j + 2 * t) * DM_) = make_float2(acc[4 * j], acc[4 * j + 2]);
            *(float2*)(pp + (size_t)(8 * j + 2 * t + 1) * DM_) = make_float2(acc[4 * j + 1], acc[4 * j + 3]);
        }
        __syncwarp();
        if (lane == 0) mbar_arrive(mb_st + 8 * (n & 3));
    }
    CAL(112 + cta, 3);
}

constexpr int N_SPARE = 16;
__global__ void __launch_bounds__(B_THREADS, 1) aux_kernel(const AuxArgs P) {
    extern __shared__ __align__(1024) unsigned char smem[];
    const uint32_t sb = __shfl_sync(0xffffffffu, smem_u32(smem), 0);
    const int warp = __shfl_sync(0xffffffffu, threadIdx.x >> 5, 0);
    const int cta = N_SPARE + blockIdx.x;
    if (threadIdx.x == 0) aux_init(sb);
    __syncthreads();
    if (warp >= 8) {
        asm volatile("setmaxnreg.dec.sync.aligned.u32 56;");
        if (warp == 11) { if (threadIdx.x == 352) aux_control(sb, cta); }
        else if (cta < NB_CTAS) aux_final(P, cta, warp - 8);
    } else {
        asm volatile("setmaxnreg.inc.sync.aligned.u32 224;");
        aux_compute(P, smem, sb, cta, warp);
    }
}

constexpr int XT_OFF = 0, WO_OFF = 81920, WO_STRIDE = 464, KV_STRIDE = 272, XB_BYTES = 32 * KV_STRIDE, QX_BYTES = 16 * KV_STRIDE,
              K_OFF = 141312, V_OFF = K_OFF + 2 * XB_BYTES, EX_OFF = V_OFF + 2 * XB_BYTES  ,
              QX_OFF = EX_OFF + XB_BYTES, QF_OFF = QX_OFF + 2 * QX_BYTES, KF_OFF = QF_OFF + 2048, VF_OFF = KF_OFF + 4096,
              IN_OFF = VF_OFF + 4096, M_OFF = IN_OFF + 3840, EX2_OFF = M_OFF + 10240 + 512  ,
              BAR_OFF = EX2_OFF + XB_BYTES, A_SMEM = BAR_OFF + 144;
constexpr int O_OFF = QF_OFF;
__device__ __forceinline__ uint32_t kv_off(int which, int role, int n) {
    const int base = which == 1 ? K_OFF : V_OFF;
    if (which != role) return base + (n & 1) * XB_BYTES;
    const int j = n % 3;
    return j == 2 ? EX_OFF : base + j * XB_BYTES;
}
__device__ __forceinline__ void tile_owner(int r, int tau, int nown, int& gr, int& rk) {
    const int q = tau < 8 ? 16 + 8 * r + tau : 6 * r + tau - 8;
    gr = q >= 2 * nown ? 2 : (q >= nown ? 1 : 0);
    rk = q - gr * nown;
    if (q >= 3 * nown) { rk = 12 + ((q - 36) >> 1); gr = (q - 36) & 1; }
}
__device__ __forceinline__ int slot_tile(int q) { return q < 16 ? 14 * (q / 6) + 8 + q % 6 : 14 * ((q - 16) >> 3) + ((q - 16) & 7); }
__host__ __device__ constexpr int korder(int i) { return i < 24 ? 14 * (i >> 3) + (i & 7) : 14 * ((i - 24) / 6) + 8 + (i - 24) % 6; }
constexpr int MB_X = BAR_OFF  , MB_M = BAR_OFF + 16  , MB_IN = BAR_OFF + 40  , MB_QC = BAR_OFF + 120, MB_H1 = BAR_OFF + 64,
              MB_KV = BAR_OFF + 72  , MB_FREE = BAR_OFF + 88  , MB_XD = BAR_OFF + 104  , MB_WO = BAR_OFF + 128;
constexpr float SCALE = 0.08838834764831845f;
constexpr float LOG2E = 1.4426950408889634f;
constexpr int A_THREADS = 384, A_CTAS = 112;

#define FRESH_LANE() int lane = lane_r; asm volatile("" : "+r"(lane)); const int g = lane >> 2, t = lane & 3; const uint32_t l16 = lane * 16; (void)g; (void)t; (void)l16
#define PIN(x) asm volatile("" ::"r"(x))
#define TS(i) do {} while (0)
#define TSV(i, cond, val) do {} while (0)

__global__ void __launch_bounds__(A_THREADS, 1)
rec_kernel(const __grid_constant__ CUtensorMap tmx, const bf16* __restrict__ mem0, const bf16* __restrict__ Wq,
           const bf16* __restrict__ Wk, const bf16* __restrict__ Wv, const bf16* __restrict__ Wo, const AuxArgs P) {
    extern __shared__ __align__(1024) unsigned char smem[];
    const uint32_t sb = __shfl_sync(0xffffffffu, smem_u32(smem), 0);
    const int tid = threadIdx.x, warp = __shfl_sync(0xffffffffu, tid >> 5, 0);
    const int lane = tid & 31;
    const int g = lane >> 2, t = lane & 3;
    uint32_t rank; asm volatile("mov.u32 %0, %%cluster_ctarank;" : "=r"(rank));
    const int cl = blockIdx.x >> 4;
    const int nh = cl < 4 ? 5 : 4;
    const int hl = rank / 3, role = rank - 3 * hl, tb = 3 * hl;
    const int head = (cl < 4 ? 5 * cl : 20 + 4 * (cl - 4)) + hl;
    const bool is_head = hl < nh;
    const int nown = 3 * nh;

    const int n_late = ((int)rank < 16) + ((int)rank + nown < 16), n_early = 3 - n_late - ((int)rank + 2 * nown >= 40);
    const int worker = cl < 4 ? cl : 4 + (cl - 4) * 4 + ((int)rank - 12);
    asm volatile("griddepcontrol.launch_dependents;");
    CAL(blockIdx.x, 0);
    if (tid == 0) {
        mbar_init(sb + MB_X, 1); mbar_init(sb + MB_X + 8, 1);
        mbar_init(sb + MB_M, 1 + n_early); mbar_init(sb + MB_M + 8, 1 + n_late);
        mbar_init(sb + MB_IN, 1); mbar_init(sb + MB_IN + 8, 1); mbar_init(sb + MB_IN + 16, 1); mbar_init(sb + MB_QC, 3);
        mbar_init(sb + MB_H1, 9); mbar_init(sb + MB_KV, 1); mbar_init(sb + MB_KV + 8, 1);
        mbar_init(sb + MB_FREE, 2); mbar_init(sb + MB_FREE + 8, 2); mbar_init(sb + MB_XD, 8); mbar_init(sb + MB_XD + 8, 8); mbar_init(sb + MB_WO, 96);
        asm volatile("fence.mbarrier_init.release.cluster;" ::: "memory");
        fence_async_smem();
        mbar_expect(sb + MB_X, 40960); mbar_expect(sb + MB_X + 8, 40960);
        if (!is_head) aux_init(sb);
    }
    __syncthreads();
    cluster_sync();
    const uint16_t tmask = (uint16_t)(7u << tb);
    if (tid == 0 && is_head) {
        for (int n = 0; n < 2; n++)
            for (int kb = role; kb < 10; kb += 3) tma3d_mc(sb + XT_OFF + n * 40960 + kb * 4096, &tmx, 0, 32 * n, kb, sb + MB_X + 8 * n, tmask);
    }

    if (warp < 8) {
        asm volatile("setmaxnreg.inc.sync.aligned.u32 224;");
        if (is_head) {
        const int lane_r = __shfl_sync(0xffffffffu, tid & 31, tid & 31);
        const int wg = warp >> 2, w = warp & 3;
        uint32_t A[40][4];
        {
            const bf16* W = role == 0 ? Wq : (role == 1 ? Wk : Wv);
            const bf16* wp = W + (size_t)(2 * t) * 4096 + head * 128 + 16 * warp + 2 * g;
#pragma unroll
            for (int ks = 0; ks < 40; ks++) {
                A[ks][0] = __ldg((const uint32_t*)(wp + (size_t)(16 * ks) * 4096));
                A[ks][1] = __ldg((const uint32_t*)(wp + (size_t)(16 * ks + 1) * 4096));
                A[ks][2] = __ldg((const uint32_t*)(wp + (size_t)(16 * ks + 8) * 4096));
                A[ks][3] = __ldg((const uint32_t*)(wp + (size_t)(16 * ks + 9) * 4096));
            }
#pragma unroll
            for (int ks = 0; ks < 40; ks++) {
                const uint32_t r0 = A[ks][0], r1 = A[ks][1], r2 = A[ks][2], r3 = A[ks][3];
                A[ks][0] = __byte_perm(r0, r1, 0x5410); A[ks][1] = __byte_perm(r0, r1, 0x7632);
                A[ks][2] = __byte_perm(r2, r3, 0x5410); A[ks][3] = __byte_perm(r2, r3, 0x7632);
            }
        }

        auto xproj = [&](int n) {
            const int st = n & 1;
            FRESH_LANE();
            const uint32_t a = sb + (role == 0 ? (st ? EX2_OFF : EX_OFF) : kv_off(role, role, n)) + (8 * (lane >> 4) + (lane & 7)) * KV_STRIDE + 32 * warp + ((lane >> 3) & 1) * 16;
            PIN(a);
            if (role == 0) { if (n >= 2) mbar_wait_u(sb + MB_QC, st); }
            else if (n >= 3) mbar_wait_u(sb + MB_FREE + 8 * ((n - 3) & 1), ((n - 3) >> 1) & 1);
            mbar_wait_u(sb + MB_X + 8 * st, (n >> 1) & 1);
            float acc[16];
            const uint32_t d0 = __shfl_sync(0xffffffffu, desc_sw128(sb + XT_OFF + st * 40960), 0);
            WG_FENCE();
#pragma unroll
            for (int ks = 0; ks < 40; ks++) wgmma_n32(acc, A[ks], d0 + (((ks >> 2) * 4096 + (ks & 3) * 32) >> 4), ks > 0);
            WG_COMMIT();
            WG_WAIT0();
            stsm4t(a, pack2(acc[0], acc[1]), pack2(acc[2], acc[3]), pack2(acc[4], acc[5]), pack2(acc[6], acc[7]));
            stsm4t(a + 16 * KV_STRIDE, pack2(acc[8], acc[9]), pack2(acc[10], acc[11]), pack2(acc[12], acc[13]), pack2(acc[14], acc[15]));
            fence_async_smem();
            __syncwarp();
            if (lane == 0) mbar_arrive(sb + MB_XD + 8 * st);
        };

        xproj(0);
        xproj(1);
#pragma unroll 1
        for (int s = 0; s < NSEG_; s++) {
            const int st = s & 1;
            if (warp == 4 && lane_r == 0) mbar_expect(sb + MB_H1, 4096);
            {
                float acc[4][4];
#pragma unroll
                for (int i = 0; i < 16; i++) ((float*)acc)[i] = 0.f;
                FRESH_LANE();
                const uint32_t mrd = sb + M_OFF + lane * 8;
                const uint32_t dl = sb + (role == 0 ? QF_OFF : (role == 1 ? KF_OFF : VF_OFF) + st * 2048) + warp * 256 + lane * 8;
                PIN(mrd); PIN(dl);
                mbar_wait_u(sb + MB_M, st);
                TS(0);
                uint2 b[40];
#pragma unroll
                for (int i = 0; i < 12; i++) b[i] = lds64(mrd + korder(i) * 256);
#pragma unroll
                for (int i = 0; i < 40; i++) {
                    if (i == LOOKW) {
                        mbar_wait_u(sb + MB_M + 8, st);
#pragma unroll
                        for (int k = 24; k < LOOKW + 12; k++) b[k] = lds64(mrd + korder(k) * 256);
                    }
                    if (i + 12 < 40 && (i + 12 < 24 || i >= LOOKW)) b[i + 12] = lds64(mrd + korder(i + 12) * 256);
                    mma16(acc[i & 3], A[korder(i)], b[i].x, b[i].y);
                }
                TS(1);
                uint32_t u0 = pack2((acc[0][0] + acc[1][0]) + (acc[2][0] + acc[3][0]), (acc[0][1] + acc[1][1]) + (acc[2][1] + acc[3][1]));
                uint32_t u1 = pack2((acc[0][2] + acc[1][2]) + (acc[2][2] + acc[3][2]), (acc[0][3] + acc[1][3]) + (acc[2][3] + acc[3][3]));
                if (role != 2) { u0 = movm(u0); u1 = movm(u1); }
                {
                    const int p1 = tb + (role == 2 ? 0 : role + 1), p2 = tb + (role == 0 ? 2 : role - 1);
                    st_async8(mapa(dl, p1), u0, u1, mapa(sb + MB_H1, p1));
                    st_async8(mapa(dl, p2), u0, u1, mapa(sb + MB_H1, p2));
                    sts64(dl, u0, u1);
                    __syncwarp();
                    if (lane == 0) mbar_arrive(sb + MB_H1);
                }
            }
            TS(2);
            if (s == NSEG_ - 1) break;
            if (s == 0) mbar_wait_u(sb + MB_WO, 0);
            uint32_t wa[8][4];
            const bool pair = wg || (w >= 2 && role != 2);
            const int tileB = wg ? 8 + w : 10 + w;
            int wA, rA, wB, rB;
            tile_owner(role, warp, nown, wA, rA); tile_owner(role, tileB, nown, wB, rB);
            uint32_t wl, inA, inB;
            {
                FRESH_LANE();
                wl = sb + WO_OFF + ((lane & 7) + (lane >> 4) * 8) * WO_STRIDE + ((lane >> 3) & 1) * 16;
                inA = mapa(sb + IN_OFF + wA * 1280 + hl * 256, rA); inB = mapa(sb + IN_OFF + wB * 1280 + hl * 256, rB);
                PIN(wl);
            }
            if (wg) {
                FRESH_LANE();
#pragma unroll
                for (int ks = 0; ks < 8; ks++) ldsm4t(wa[ks], wl + warp * 32 + ks * 16 * WO_STRIDE);
                if (w < 2) {
                    mbar_wait_u(sb + MB_H1, st);
                    if (lane == 0) {
                        if (w == 0) {
                            mbar_expect(sb + MB_M, 6144 - 256 * n_early); mbar_expect(sb + MB_M + 8, 4096 - 256 * n_late);
                        }
                        else {
                            for (int n = (s == 0 ? 2 : s + 3); n <= s + 3 && n < NSEG_; n++) {
                                mbar_expect(sb + MB_X + 8 * (n & 1), 40960);
                                for (int kb = role; kb < 10; kb += 3)
                                    tma3d_mc(sb + XT_OFF + (n & 1) * 40960 + kb * 4096, &tmx, 0, 32 * n, kb, sb + MB_X + 8 * (n & 1), tmask);
                            }
                        }
                    }
                    __syncwarp();
                }
            } else {
                FRESH_LANE();
                const uint32_t s_base = sb + M_OFF + role * 3584;
                const uint32_t r8 = (lane & 7) * KV_STRIDE;
                const int mt = w & 1, eh = w >> 1;
                mbar_wait_u(sb + MB_KV + 8 * st, (s >> 1) & 1);
                if (w == 3 && lane == 0) asm volatile("mbarrier.arrive.relaxed.cluster.shared::cluster.b64 _, [%0];" ::"r"(mapa(sb + MB_QC, tb)) : "memory");
                uint32_t vb[2][2][4];
                uint2 vm[2];
                {
                    const uint32_t ka = sb + kv_off(1, role, s) + eh * 128 + r8 + (16 * mt + ((lane >> 3) & 1) * 8) * KV_STRIDE + (lane >> 4) * 16;
                    const uint32_t fl = sb + lane * 8;
                    const uint32_t sw = s_base + eh * 1280 + mt * 64 + t * 320 + g * 4;
                    const uint32_t sm = s_base + 2560 + w * 256 + t * 64 + g * 4;
                    uint32_t a[4][4];
#pragma unroll
                    for (int k = 0; k < 4; k++) ldsm4(a[k], ka + k * 32);
                    const uint32_t va1 = sb + kv_off(2, role, s) + w * 64 + r8 + ((lane >> 3) & 1) * 8 * KV_STRIDE + (lane >> 4) * 16;
                    ldsm4t(vb[0][0], va1); ldsm4t(vb[0][1], va1 + 32);
                    ldsm4t(vb[1][0], va1 + 16 * KV_STRIDE); ldsm4t(vb[1][1], va1 + 16 * KV_STRIDE + 32);
                    PIN(fl); PIN(sw); PIN(sm);
                    mbar_wait_u(sb + MB_H1, st);
                    TS(3);
                    uint2 b[4], am[2], bm[2];
#pragma unroll
                    for (int k = 0; k < 4; k++) b[k] = lds64(fl + QF_OFF + (4 * eh + k) * 256);
#pragma unroll
                    for (int k = 0; k < 2; k++) { am[k] = lds64(fl + KF_OFF + st * 2048 + (2 * w + k) * 256); bm[k] = lds64(fl + QF_OFF + (2 * w + k) * 256); }
                    float c0[4] = {0, 0, 0, 0}, c1[4] = {0, 0, 0, 0}, c2[4] = {0, 0, 0, 0}, c3[4] = {0, 0, 0, 0};
                    mma16(c0, a[0], b[0].x, b[0].y); mma16(c1, a[1], b[1].x, b[1].y);
                    mma16r(c2, am[0].x, 0u, am[0].y, 0u, bm[0].x, bm[0].y);
                    mma16r(c3, am[1].x, 0u, am[1].y, 0u, bm[1].x, bm[1].y);
                    mma16(c0, a[2], b[2].x, b[2].y); mma16(c1, a[3], b[3].x, b[3].y);
                    sts32f(sm, c2[0] + c3[0]); sts32f(sm + 32, c2[1] + c3[1]);
                    sts32f(sw, c0[0] + c1[0]); sts32f(sw + 160, c0[1] + c1[1]);
                    sts32f(sw + 32, c0[2] + c1[2]); sts32f(sw + 160 + 32, c0[3] + c1[3]);
#pragma unroll
                    for (int k = 0; k < 2; k++) vm[k] = lds64(fl + VF_OFF + st * 2048 + (2 * w + k) * 256);
                }
                const uint32_t sr = s_base + g * 160 + t * 8;
                bar_sync(7, 128);
                TS(4);
                float sc[10];
                {
                    float2 m[4], p0[4], p1[4];
#pragma unroll
                    for (int j = 0; j < 4; j++) { p0[j] = lds64f(sr + j * 32); p1[j] = lds64f(sr + 1280 + j * 32); }
#pragma unroll
                    for (int j = 0; j < 4; j++) m[j] = lds64f(s_base + 2560 + j * 256 + lane * 8);
#pragma unroll
                    for (int j = 0; j < 4; j++) { sc[2 + 2 * j] = p0[j].x + p1[j].x; sc[3 + 2 * j] = p0[j].y + p1[j].y; }
                    sc[0] = (m[0].x + m[1].x) + (m[2].x + m[3].x); sc[1] = (m[0].y + m[1].y) + (m[2].y + m[3].y);
                }
                float mx = fmaxf(fmaxf(fmaxf(sc[2], sc[3]), fmaxf(sc[4], sc[5])), fmaxf(fmaxf(sc[6], sc[7]), fmaxf(sc[8], sc[9])));
                mx = fmaxf(mx, fmaxf(sc[0], sc[1]));
                mx = fmaxf(mx, __shfl_xor_sync(~0u, mx, 1)); mx = fmaxf(mx, __shfl_xor_sync(~0u, mx, 2));
                const float nm = -mx * (SCALE * LOG2E);
#pragma unroll
                for (int i = 0; i < 10; i++) sc[i] = ex2(fmaf(sc[i], SCALE * LOG2E, nm));
                uint32_t p[5];
#pragma unroll
                for (int j = 0; j < 5; j++) p[j] = pack2(sc[2 * j], sc[2 * j + 1]);
                float o[4][4];
#pragma unroll
                for (int i = 0; i < 16; i++) ((float*)o)[i] = 0.f;
#pragma unroll
                for (int n = 0; n < 4; n++) mma8(o[n], p[0], 0u, (n & 1) ? vm[n >> 1].y : vm[n >> 1].x);
#pragma unroll
                for (int n = 0; n < 4; n++) mma16r(o[n], p[1], 0u, p[2], 0u, vb[0][n >> 1][2 * (n & 1)], vb[0][n >> 1][2 * (n & 1) + 1]);
#pragma unroll
                for (int n = 0; n < 4; n++) mma16r(o[n], p[3], 0u, p[4], 0u, vb[1][n >> 1][2 * (n & 1)], vb[1][n >> 1][2 * (n & 1) + 1]);
                float sum = ((sc[0] + sc[1]) + (sc[2] + sc[3])) + ((sc[4] + sc[5]) + (sc[6] + sc[7])) + (sc[8] + sc[9]);
                sum += __shfl_xor_sync(~0u, sum, 1); sum += __shfl_xor_sync(~0u, sum, 2);
                const float inv = rcp(sum);
                sts128(sb + O_OFF + w * 512 + l16,
                       make_uint4(pack2(o[0][0] * inv, o[0][1] * inv), pack2(o[1][0] * inv, o[1][1] * inv),
                                  pack2(o[2][0] * inv, o[2][1] * inv), pack2(o[3][0] * inv, o[3][1] * inv)));
#pragma unroll
                for (int ks = 0; ks < 8; ks++) ldsm4t(wa[ks], wl + warp * 32 + ks * 16 * WO_STRIDE);
            }
            {
            FRESH_LANE();
            bar_sync(1, 256);
            TS(5);
            uint4 ob[4];
#pragma unroll
            for (int k = 0; k < 4; k++) ob[k] = lds128(sb + O_OFF + k * 512 + l16);
            float d[2][4];
#pragma unroll
            for (int i = 0; i < 8; i++) ((float*)d)[i] = 0.f;
#pragma unroll
            for (int k = 0; k < 4; k++) {
                mma16(d[0], wa[2 * k], ob[k].x, ob[k].y); mma16(d[1], wa[2 * k + 1], ob[k].z, ob[k].w);
                if (pair) { ldsm4t(wa[2 * k], wl + tileB * 32 + (2 * k) * 16 * WO_STRIDE); ldsm4t(wa[2 * k + 1], wl + tileB * 32 + (2 * k + 1) * 16 * WO_STRIDE); }
            }
            st_async8(inA + lane * 8, pack2(d[0][0] + d[1][0], d[0][1] + d[1][1]), pack2(d[0][2] + d[1][2], d[0][3] + d[1][3]), mapa(sb + MB_IN + 8 * wA, rA));
            if (pair) {
#pragma unroll
                for (int i = 0; i < 8; i++) ((float*)d)[i] = 0.f;
#pragma unroll
                for (int k = 0; k < 4; k++) { mma16(d[0], wa[2 * k], ob[k].x, ob[k].y); mma16(d[1], wa[2 * k + 1], ob[k].z, ob[k].w); }
                st_async8(inB + lane * 8, pack2(d[0][0] + d[1][0], d[0][1] + d[1][1]), pack2(d[0][2] + d[1][2], d[0][3] + d[1][3]), mapa(sb + MB_IN + 8 * wB, rB));
            }
            }
            TS(6);
            TSV(14, threadIdx.x == 224, clk());
            if (s + 2 < NSEG_) xproj(s + 2);
            else mbar_wait_u(sb + MB_FREE + 8, 0);
            TS(7);
        }
        if (warp == 0) { mbar_wait_u(sb + MB_H1, 1); mbar_wait_u(sb + MB_KV + 8, 1); mbar_wait_u(sb + MB_FREE, 1); mbar_wait_u(sb + MB_FREE + 8, 1); if (role == 0) mbar_wait_u(sb + MB_QC, 0); }
        }
        else aux_compute(P, smem, sb, worker, warp);
    } else {
      asm volatile("setmaxnreg.dec.sync.aligned.u32 56;");
      if (warp < 11) {
        const int cw = warp - 8, ct = cw * 32 + lane;
        const int q = is_head ? cw * nown + (int)rank : 36 + ((int)rank - 12) * 2 + cw, idx = is_head ? rank : 3 * cw;
        const bool own = is_head ? q < 40 : (nh == 4 && rank < 14 && cw < 2);
        const int T = slot_tile(q);
        if (own) st_rel8(&g_X[2][(T * 7 + cl) * 32 + lane], 0u, 0u);
        if (is_head) {
            uint2 mv[14];
#pragma unroll
            for (int j = 0; j < 14; j++) {
                const int p = min(ct + 96 * j, 1279), ks = p >> 5, l = p & 31;
                const uint32_t* mp = (const uint32_t*)(mem0 + (l >> 2) * DM_ + ks * 16 + 2 * (l & 3));
                mv[j] = make_uint2(__ldg(mp), __ldg(mp + 4));
            }
            const int nch = role == 2 ? 24 : 28;
            for (int r = cw; r < 128; r += 3) {
                if (lane < nch) cp_async16(sb + WO_OFF + r * WO_STRIDE + lane * 16, Wo + (size_t)(head * 128 + eperm(r)) * DM_ + role * 224 + lane * 8);
            }
            asm volatile("cp.async.mbarrier.arrive.noinc.shared.b64 [%0];" ::"r"(sb + MB_WO) : "memory");
#pragma unroll
            for (int j = 0; j < 14; j++) {
                const int p = min(ct + 96 * j, 1279);
                sts64(sb + M_OFF + p * 8, mv[j].x, mv[j].y);
            }
            bar_sync(6, 96);
            if (ct == 0) {
                for (int j = 0; j <= n_early; j++) mbar_arrive(sb + MB_M);
                for (int j = 0; j <= n_late; j++) mbar_arrive(sb + MB_M + 8);
            }
        }
        __threadfence();
        const bool sender = is_head && cw == 2;
        auto send_x = [&](int n) {
            const int st = n & 1;
            mbar_wait_u(sb + MB_XD + 8 * st, (n >> 1) & 1);
            if (n >= 1) mbar_wait_u(sb + MB_H1, (n - 1) & 1);
            if (n >= 2) mbar_wait_u(sb + MB_FREE + 8 * st, ((n - 2) >> 1) & 1);
            const int a0 = (2 * n) % 3, a1 = (2 * n + 1) % 3;
            const uint32_t mbkv = sb + MB_KV + 8 * st, qs = sb + (st ? EX2_OFF : EX_OFF);
            if (lane == 0) {
                if (role == 0) {
                    if (a0 != 0) bulk_s2s(mapa(sb + QX_OFF + st * QX_BYTES, tb + a0), qs, QX_BYTES, mapa(mbkv, tb + a0));
                    if (a1 != 0) bulk_s2s(mapa(sb + QX_OFF + st * QX_BYTES, tb + a1), qs + QX_BYTES, QX_BYTES, mapa(mbkv, tb + a1));
                } else {
                    const uint32_t src = sb + kv_off(role, role, n), dst = sb + kv_off(role, 0, n);
                    bulk_s2s(mapa(dst, tb), src, XB_BYTES, mapa(mbkv, tb));
                    bulk_s2s(mapa(dst, tb + 3 - role), src, XB_BYTES, mapa(mbkv, tb + 3 - role));
                }
            }
            if (role == 0 && (a0 == 0 || a1 == 0)) {
                const uint32_t src = qs + (a0 == 0 ? 0 : QX_BYTES);
                for (int i = lane; i < QX_BYTES / 16; i += 32) sts128(sb + QX_OFF + st * QX_BYTES + i * 16, lds128(src + i * 16));
            }
            __syncwarp();
            if (lane == 0) mbar_expect(mbkv, (role == 0 ? 2 * XB_BYTES : XB_BYTES) + (role != 0 && (a0 == role || a1 == role) ? QX_BYTES : 0));
            __syncwarp();
        };
        if (sender) send_x(0);
        if (own || sender) {
            const uint32_t mdst = sb + M_OFF + T * 256 + lane * 8;
            const uint32_t mbar = sb + MB_M + (q < 16 ? 8 : 0);
            if (own && lane == 0) mbar_expect(sb + MB_IN + 8 * cw, nh * 256);
#pragma unroll 1
            for (int s = 0; s < NSEG_ - 1; s++) {
                if (sender) send_x(s + 1);
                if (!own) continue;
                int lane_o = lane;
                asm volatile("" : "+r"(lane_o));
                uint2* xs = &g_X[s & 3][T * 7 * 32 + lane_o];
                uint2* xw = xs + cl * 32;
                const uint32_t ib = sb + IN_OFF + cw * 1280 + lane_o * 8;
                asm volatile("" ::"l"(xw), "r"(ib));
                mbar_wait_u(sb + MB_IN + 8 * cw, s & 1);
                TS(10);
                uint2 v[7];
                {
                    uint2 q5[5];
#pragma unroll
                    for (int h = 0; h < 4; h++) q5[h] = lds64(ib + h * 256);
                    q5[4] = make_uint2(0, 0);
                    if (nh == 5) q5[4] = lds64(ib + 1024);
#define SUM5(f, c) ((f(q5[0].c) + f(q5[1].c)) + (f(q5[2].c) + f(q5[3].c)) + f(q5[4].c))
                    const uint32_t o0 = nzw(pack2(SUM5(bflo, x), SUM5(bfhi, x))), o1 = nzw(pack2(SUM5(bflo, y), SUM5(bfhi, y)));
                    st_rel8(xw, o0, o1);
#pragma unroll
                    for (int c = 0; c < 7; c++) v[c] = c == cl ? make_uint2(o0, o1) : make_uint2(0, 0);
                }
                const int tw = clk();
                TS(11);
                if (lane == 0) mbar_expect(sb + MB_IN + 8 * cw, nh * 256);
                while (clk() - tw < DELAY_X) {}
                int guard = 0;
                while (true) {
                    uint32_t chk = 0xffffffffu;
#pragma unroll
                    for (int c = 0; c < 7; c++) if (min(v[c].x, v[c].y) == 0) v[c] = ld_poll8(xs + c * 32);
#pragma unroll
                    for (int c = 0; c < 7; c++) chk = min(chk, min(v[c].x, v[c].y));
                    if (!__any_sync(~0u, chk == 0)) break;
                    if (++guard > SPIN_LIMIT) { g_misc[2] = 2; break; }
                }
                TS(12);
#define SUM7(f, c) (((f(v[0].c) + f(v[1].c)) + (f(v[2].c) + f(v[3].c))) + ((f(v[4].c) + f(v[5].c)) + f(v[6].c)))
                const uint32_t b0 = movm(pack2(SUM7(bflo, x), SUM7(bfhi, x))), b1 = movm(pack2(SUM7(bflo, y), SUM7(bfhi, y)));
                int d = idx;
                if (!is_head) st_async8(mapa(mdst, d), b0, b1, mapa(mbar, d));
#pragma unroll
                for (int r = 1; r < 15; r++) {
                    d = d + 1 == nown ? 0 : d + 1;
                    if (r < 12 || nh == 5) st_async8(mapa(mdst, d), b0, b1, mapa(mbar, d));
                }
                if (is_head) { sts64(mdst, b0, b1); __syncwarp(); if (lane == 0) mbar_arrive(mbar); }
                TS(13);
                TSV(15, threadIdx.x == 256, guard);
                if (s > 0) { st_rel8(&g_X[(s - 1) & 3][(T * 7 + cl) * 32 + lane_o], 0u, 0u); __threadfence(); }
            }
        }
        if (!is_head && (!aux_quiet(worker) || (cw == 2 && aux_vid(worker) == 25))) aux_final(P, worker, cw);
      } else if (is_head) {
        unsigned* cnt = &g_oxcnt[cl];
        int pending = -1;
#pragma unroll 1
        for (int task = role; task < 2 * NSEG_; task += 3) {
            const int s = task >> 1, mt = task & 1;
            const int st = s & 1;
            mbar_wait_u(sb + MB_KV + 8 * st, (s >> 1) & 1);
            mbar_wait_u(sb + MB_H1, st);
            TS(8);
            int lane = threadIdx.x & 31;
            asm volatile("" : "+r"(lane));
            const int g = lane >> 2, t = lane & 3;
            float sc[5][4];
#pragma unroll
            for (int i = 0; i < 20; i++) ((float*)sc)[i] = 0.f;
            const uint32_t r8 = (lane & 7) * KV_STRIDE;
            {
                const uint32_t qa = sb + QX_OFF + st * QX_BYTES + ((lane >> 3) & 1) * 8 * KV_STRIDE + r8 + (lane >> 4) * 16;
                const uint32_t ka = sb + kv_off(1, role, s) + r8 + ((lane >> 3) & 1) * 16 + (lane >> 4) * 8 * KV_STRIDE;
                const uint32_t kf = sb + KF_OFF + st * 2048 + lane * 8;
                uint32_t a[2][4], b0[2][4], b1[2][4]; uint2 bm[2];
                ldsm4(a[0], qa); bm[0] = lds64(kf); ldsm4(b0[0], ka); ldsm4(b1[0], ka + 16 * KV_STRIDE);
#pragma unroll
                for (int ks = 0; ks < 8; ks++) {
                    const int c = ks & 1, n = c ^ 1;
                    if (ks < 7) {
                        ldsm4(a[n], qa + (ks + 1) * 32); bm[n] = lds64(kf + (ks + 1) * 256);
                        ldsm4(b0[n], ka + (ks + 1) * 32); ldsm4(b1[n], ka + 16 * KV_STRIDE + (ks + 1) * 32);
                    }
                    mma16(sc[0], a[c], bm[c].x, bm[c].y);
                    mma16(sc[1], a[c], b0[c][0], b0[c][1]); mma16(sc[2], a[c], b0[c][2], b0[c][3]);
                    if (mt) { mma16(sc[3], a[c], b1[c][0], b1[c][1]); mma16(sc[4], a[c], b1[c][2], b1[c][3]); }
                }
            }
            uint32_t p[5][2];
#pragma unroll
            for (int h = 0; h < 2; h++) {
                const int lim = 8 + 16 * mt + g + 8 * h - 2 * t;
                float mx = -3.0e38f;
#pragma unroll
                for (int j = 0; j < 5; j++) {
                    uint32_t r1 = pack2(sc[j][2 * h], sc[j][2 * h + 1]);
                    r1 = pack2(bflo(r1) * SCALE, bfhi(r1) * SCALE);
                    const float v0 = (8 * j <= lim) ? bflo(r1) : -1.0e9f, v1 = (8 * j + 1 <= lim) ? bfhi(r1) : -1.0e9f;
                    sc[j][2 * h] = v0; sc[j][2 * h + 1] = v1; mx = fmaxf(mx, fmaxf(v0, v1));
                }
                mx = fmaxf(mx, __shfl_xor_sync(~0u, mx, 1)); mx = fmaxf(mx, __shfl_xor_sync(~0u, mx, 2));
                float sum = 0.f;
#pragma unroll
                for (int j = 0; j < 5; j++) {
#pragma unroll
                    for (int i = 0; i < 2; i++) { float e = ex2((sc[j][2 * h + i] - mx) * LOG2E); sc[j][2 * h + i] = e; sum += e; }
                }
                sum += __shfl_xor_sync(~0u, sum, 1); sum += __shfl_xor_sync(~0u, sum, 2);
                const float inv = rcp(sum);
#pragma unroll
                for (int j = 0; j < 5; j++) p[j][h] = pack2(sc[j][2 * h] * inv, sc[j][2 * h + 1] * inv);
            }
            uint32_t* og = (uint32_t*)(g_ox + (size_t)(s * NH_ + head) * 512) + (16 * mt + g) * 32 + t;
            const uint32_t va = sb + kv_off(2, role, s) + r8 + ((lane >> 3) & 1) * 8 * KV_STRIDE + (lane >> 4) * 16;
            const uint32_t vf = sb + VF_OFF + st * 2048 + lane * 8;
            {
                uint32_t b0[2][4], b1[2][4]; uint2 bm[2];
                bm[0] = lds64(vf); ldsm4t(b0[0], va); ldsm4t(b1[0], va + 16 * KV_STRIDE);
#pragma unroll
                for (int np = 0; np < 8; np++) {
                    const int c = np & 1, nx = c ^ 1;
                    if (np < 7) { bm[nx] = lds64(vf + (np + 1) * 256); ldsm4t(b0[nx], va + (np + 1) * 32); ldsm4t(b1[nx], va + 16 * KV_STRIDE + (np + 1) * 32); }
                    float o[2][4] = {{0, 0, 0, 0}, {0, 0, 0, 0}};
                    mma8(o[0], p[0][0], p[0][1], bm[c].x); mma8(o[1], p[0][0], p[0][1], bm[c].y);
                    mma16r(o[0], p[1][0], p[1][1], p[2][0], p[2][1], b0[c][0], b0[c][1]);
                    mma16r(o[1], p[1][0], p[1][1], p[2][0], p[2][1], b0[c][2], b0[c][3]);
                    if (mt) {
                        mma16r(o[0], p[3][0], p[3][1], p[4][0], p[4][1], b1[c][0], b1[c][1]);
                        mma16r(o[1], p[3][0], p[3][1], p[4][0], p[4][1], b1[c][2], b1[c][3]);
                    }
#pragma unroll
                    for (int n = 0; n < 2; n++) {
                        const int ch = (2 * np + n) & 7;
                        int gx = g; asm volatile("" : "+r"(gx));
                        uint32_t* o2 = og + (np >> 2) * 1024 + ((ch ^ gx) << 2);
                        o2[0] = pack2(o[n][0], o[n][1]);
                        o2[256] = pack2(o[n][2], o[n][3]);
                    }
                }
            }
            __syncwarp();
            if (lane < 3) asm volatile("mbarrier.arrive.relaxed.cluster.shared::cluster.b64 _, [%0];" ::"r"(mapa(sb + MB_FREE + 8 * st, tb + lane)) : "memory");
            if (mt == 0 && task + 9 < 2 * NSEG_) pending = s;
            else {
                if (lane == 0) {
                    asm volatile("fence.acq_rel.gpu;" ::: "memory");
                    asm volatile("red.relaxed.gpu.global.add.u32 [%0], 1;" ::"l"(cnt + s * 8) : "memory");
                    if (pending >= 0) asm volatile("red.relaxed.gpu.global.add.u32 [%0], 1;" ::"l"(cnt + pending * 8) : "memory");
                }
                pending = -1;
            }
            __syncwarp();
            TS(9);
        }
      }
      else if (lane == 0) aux_control(sb, worker);
    }
    __syncthreads();
    CAL(blockIdx.x, 1);
    cluster_sync();
}

__device__ bf16 f_mem[2][8 * DM_];
__device__ bf16 f_qkv[3][40 * 4096];
__device__ bf16 f_o[40 * 4096];
__global__ void fb_conv(const AuxArgs P) {
    __shared__ float u[S_], kk[S_];
    const int c = blockIdx.x;
    for (int t = threadIdx.x; t < S_; t += 256) {
        float a = 0.f;
        for (int tt = 0; tt < 4; tt++) { const int r = t + tt - 3; const float kv = r >= 0 ? __bfloat162float(P.Bk[(size_t)r * DM_ + c]) : 0.f; a = rbf(a + rbf(kv * __bfloat162float(P.shk[c * 4 + 3 - tt]))); }
        u[t] = rbf(a * __bfloat162float(P.Bv[(size_t)t * DM_ + c])); kk[t] = __bfloat162float(P.ssmk[(size_t)c * S_ + t]);
    }
    __syncthreads();
    const float D = __bfloat162float(P.ssmD[c]);
    for (int t = threadIdx.x; t < S_; t += 256) {
        float y = 0.f;
        for (int j = 0; j <= t; j++) y = fmaf(u[j], kk[t - j], y);
        g_b[(size_t)t * DM_ + c] = __float2bfloat16_rn(__bfloat162float(P.x[(size_t)t * DM_ + c]) * rbf(rbf(y) + rbf(u[t] * D)));
    }
}
__global__ void fb_proj(const bf16* x, const bf16* mem, const bf16* Wq, const bf16* Wk, const bf16* Wv, int s) {
    __shared__ bf16 h[40][DM_ / 2];
    const bf16* W = blockIdx.y == 0 ? Wq : (blockIdx.y == 1 ? Wk : Wv);
    const int col = blockIdx.x * 128 + threadIdx.x;
    float acc[40];
    for (int r = 0; r < 40; r++) acc[r] = 0.f;
    for (int half = 0; half < 2; half++) {
        __syncthreads();
        for (int i = threadIdx.x; i < 40 * 320; i += 128) { const int r = i / 320, d = i % 320 + half * 320; h[r][i % 320] = r < 8 ? mem[r * DM_ + d] : x[(size_t)(s * 32 + r - 8) * DM_ + d]; }
        __syncthreads();
        for (int d = 0; d < 320; d++) {
            const float wv = __bfloat162float(W[(size_t)(d + half * 320) * 4096 + col]);
#pragma unroll
            for (int r = 0; r < 40; r++) acc[r] = fmaf(__bfloat162float(h[r][d]), wv, acc[r]);
        }
    }
    for (int r = 0; r < 40; r++) f_qkv[blockIdx.y][r * 4096 + col] = __float2bfloat16_rn(acc[r]);
}
__global__ void fb_attn() {
    __shared__ float p[40][41];
    const int hb = blockIdx.x * 128;
    for (int i = threadIdx.x; i < 1600; i += 128) {
        const int q = i / 40, k = i % 40; float a = 0.f;
        for (int e = 0; e < 128; e++) a = fmaf(__bfloat162float(f_qkv[0][q * 4096 + hb + e]), __bfloat162float(f_qkv[1][k * 4096 + hb + e]), a);
        p[q][k] = (q < 8 || q >= k) ? rbf(rbf(a) * 0.08838834764831845f) : -1.0e9f;
    }
    __syncthreads();
    if (threadIdx.x < 40) {
        float* r = p[threadIdx.x]; float mx = r[0], sum = 0.f;
        for (int k = 1; k < 40; k++) mx = fmaxf(mx, r[k]);
        for (int k = 0; k < 40; k++) { r[k] = expf(r[k] - mx); sum += r[k]; }
        for (int k = 0; k < 40; k++) r[k] = rbf(r[k] / sum);
    }
    __syncthreads();
    for (int q = 0; q < 40; q++) {
        float a = 0.f;
        for (int k = 0; k < 40; k++) a = fmaf(p[q][k], __bfloat162float(f_qkv[2][k * 4096 + hb + threadIdx.x]), a);
        f_o[q * 4096 + hb + threadIdx.x] = __float2bfloat16_rn(a);
    }
}
__global__ void fb_out(const AuxArgs P, bf16* memn, int s) {
    __shared__ float o[4096]; __shared__ float red[128];
    const int r = blockIdx.x, c = blockIdx.y * 128 + threadIdx.x;
    for (int i = threadIdx.x; i < 4096; i += 128) o[i] = __bfloat162float(f_o[r * 4096 + i]);
    const int row = s * 32 + r - 8;
    float ga = 0.f;
    if (r >= 8) for (int d = threadIdx.x; d < DM_; d += 128) ga += rbf(__bfloat162float(P.x[(size_t)row * DM_ + d]) * __bfloat162float(P.gatew[d]));
    red[threadIdx.x] = ga;
    __syncthreads();
    float a = 0.f;
    for (int k = 0; k < 4096; k++) a = fmaf(o[k], __bfloat162float(P.Wo[(size_t)k * DM_ + c]), a);
    if (r < 8) { memn[r * DM_ + c] = __float2bfloat16_rn(a); return; }
    ga = 0.f; for (int i = 0; i < 128; i++) ga += red[i];
    const float gt = rbf(1.f / (1.f + expf(-rbf(ga)))), og = rbf(1.f - gt);
    P.out[(size_t)row * DM_ + c] = __float2bfloat16_rn(rbf(gt * rbf(a)) + rbf(og * __bfloat162float(g_b[(size_t)row * DM_ + c])));
}

typedef CUresult (*EncodeFn)(CUtensorMap*, CUtensorMapDataType, cuuint32_t, void*, const cuuint64_t*, const cuuint64_t*,
                             const cuuint32_t*, const cuuint32_t*, CUtensorMapInterleave, CUtensorMapSwizzle,
                             CUtensorMapL2promotion, CUtensorMapFloatOOBfill);

extern "C" void kernel_launch(void* const* d_in, const int* in_sizes, int n_in, void* d_out, int out_size) {
    const bf16* x = (const bf16*)d_in[0];
    const bf16* mem0 = (const bf16*)d_in[1];
    const bf16* Wq = (const bf16*)d_in[2];
    const bf16* Wk = (const bf16*)d_in[3];
    const bf16* Wv = (const bf16*)d_in[4];
    const bf16* Wo = (const bf16*)d_in[5];
    const bf16* Bk = (const bf16*)d_in[8];
    const bf16* Bv = (const bf16*)d_in[9];
    const bf16* shk = (const bf16*)d_in[10];
    const bf16* ssmk = (const bf16*)d_in[11];
    const bf16* ssmD = (const bf16*)d_in[12];
    const bf16* gatew = (const bf16*)d_in[13];

    static EncodeFn enc = nullptr;
    static int fast = -1;
    if (fast < 0) {
        void* fn = nullptr; cudaDriverEntryPointQueryResult qr;
        cudaGetDriverEntryPoint("cuTensorMapEncodeTiled", &fn, cudaEnableDefault, &qr);
        enc = (EncodeFn)fn;
        cudaFuncSetAttribute(rec_kernel, cudaFuncAttributeMaxDynamicSharedMemorySize, A_SMEM + 1024);
        cudaFuncSetAttribute(rec_kernel, cudaFuncAttributeNonPortableClusterSizeAllowed, 1);
        cudaFuncSetAttribute(aux_kernel, cudaFuncAttributeMaxDynamicSharedMemorySize, B_SMEM);
        cudaLaunchConfig_t qc = {};
        qc.gridDim = dim3(A_CTAS); qc.blockDim = dim3(A_THREADS); qc.dynamicSmemBytes = A_SMEM + 1024;
        cudaLaunchAttribute qa[1];
        qa[0].id = cudaLaunchAttributeClusterDimension; qa[0].val.clusterDim.x = 16; qa[0].val.clusterDim.y = 1; qa[0].val.clusterDim.z = 1;
        qc.attrs = qa; qc.numAttrs = 1;
        int ncl = 0, nsm = 0, dev = 0;
        cudaGetDevice(&dev);
        cudaDeviceGetAttribute(&nsm, cudaDevAttrMultiProcessorCount, dev);
        if (cudaOccupancyMaxActiveClusters(&ncl, rec_kernel, &qc) != cudaSuccess) { ncl = 0; cudaGetLastError(); }
        fast = (enc != nullptr && ncl >= 7 && nsm >= A_CTAS + NB_CTAS - N_SPARE + 1) ? 1 : 0;
    }
    if (!fast) {
        cudaStream_t fs = cudaStreamPerThread;
        AuxArgs FP = {x, Wo, Bk, Bv, shk, ssmk, ssmD, gatew, (bf16*)d_out};
        bf16* fm; cudaGetSymbolAddress((void**)&fm, f_mem);
        fb_conv<<<DM_, 256, 0, fs>>>(FP);
        for (int s = 0; s < NSEG_; s++) {
            fb_proj<<<dim3(32, 3), 128, 0, fs>>>(x, s == 0 ? mem0 : fm + (s & 1) * 8 * DM_, Wq, Wk, Wv, s);
            fb_attn<<<32, 128, 0, fs>>>();
            fb_out<<<dim3(40, 5), 128, 0, fs>>>(FP, fm + ((s + 1) & 1) * 8 * DM_, s);
        }
        return;
    }
    CUtensorMap tmx;
    {
        cuuint64_t dims[3] = {64, (cuuint64_t)S_, 10};
        cuuint64_t strides[2] = {DM_ * 2, 128};
        cuuint32_t box[3] = {64, 32, 1}, es[3] = {1, 1, 1};
        enc(&tmx, CU_TENSOR_MAP_DATA_TYPE_BFLOAT16, 3, (void*)x, dims, strides, box, es, CU_TENSOR_MAP_INTERLEAVE_NONE,
            CU_TENSOR_MAP_SWIZZLE_128B, CU_TENSOR_MAP_L2_PROMOTION_L2_256B, CU_TENSOR_MAP_FLOAT_OOB_FILL_NONE);
    }
    cudaStream_t st = cudaStreamPerThread;
    AuxArgs P = {x, Wo, Bk, Bv, shk, ssmk, ssmD, gatew, (bf16*)d_out};
    {
        cudaLaunchConfig_t ca = {};
        ca.gridDim = dim3(A_CTAS); ca.blockDim = dim3(A_THREADS); ca.dynamicSmemBytes = A_SMEM + 1024; ca.stream = st;
        cudaLaunchAttribute aa[1];
        aa[0].id = cudaLaunchAttributeClusterDimension; aa[0].val.clusterDim.x = 16; aa[0].val.clusterDim.y = 1; aa[0].val.clusterDim.z = 1;
        ca.attrs = aa; ca.numAttrs = 1;
        cudaLaunchKernelEx(&ca, rec_kernel, tmx, mem0, Wq, Wk, Wv, Wo, P);
    }
    cudaLaunchConfig_t cfg = {};
    cfg.gridDim = dim3(NB_CTAS - N_SPARE + 1);
    cfg.blockDim = dim3(B_THREADS); cfg.dynamicSmemBytes = B_SMEM; cfg.stream = st;
    cudaLaunchAttribute at[1];
    at[0].id = cudaLaunchAttributeProgrammaticStreamSerialization; at[0].val.programmaticStreamSerializationAllowed = 1;
    cfg.attrs = at; cfg.numAttrs = 1;
    cudaLaunchKernelEx(&cfg, aux_kernel, P);
}
```
